```python
import torch

def _softmax(x, axis=-1):
    return torch.softmax(x, dim=axis)
def _gelu(x):
    return torch.nn.functional.gelu(x, approximate="tanh")
def _silu(x):
    return torch.nn.functional.silu(x)
def _sigmoid(x):
    return torch.sigmoid(x)
def _layernorm(x, axis=-1, eps=1e-5):
    m = x.mean(dim=axis, keepdim=True)
    v = x.var(dim=axis, keepdim=True, unbiased=False)
    return (x - m) / torch.sqrt(v + eps)
def _scatter_add(tgt, idx, src, axis=0):
    return tgt.clone().index_add_(axis, idx, src)
def _segment_sum(src, seg, n):
    out = torch.zeros((n,) + src.shape[1:], dtype=src.dtype)
    return out.index_add_(0, seg, src)
def _pad(x, pw):
    flat = tuple(v for pair in reversed(pw) for v in pair)
    return torch.nn.functional.pad(x, flat)

kernel_name = 'standalone__weight_only_int_gptq__prompt'

def setup_inputs():

    _w = (lambda a: (lambda t: t.to(torch.bfloat16) if t.is_floating_point() else t)(torch.as_tensor(a)))
    B, S, D, F = 1, 2048, 576, 4608
    bits = max(2, min(4, 3))
    pf = 32 // bits
    G = -1 if -1 > 0 else D
    G = max(pf, (G // pf) * pf)
    D = max(G, (D // G) * G)
    ng = D // G
    qmax = 1 << bits
    qw = torch.randint(0, qmax, (D, F)).to(torch.int64)
    packed = torch.zeros((D // pf, F), dtype=torch.int64)
    for i in range(pf):
        packed |= (qw[i::pf] << (i * bits))
    packed = packed.to(torch.int32)
    return {
        "x": _w((lambda *s: torch.randn(*s, dtype=torch.bfloat16) * 0.05)(B, S, D)),
        "qw_packed": _w(packed),
        "scales": _w(torch.abs((lambda *s: torch.randn(*s, dtype=torch.bfloat16) * 0.05)(ng, F)).to(float) * 0.1 + 0.01),
        "zeros": _w(torch.randint(0, qmax, (ng, F)).to(float)),
        "bits": _w((lambda _x: torch.as_tensor(_x, dtype=torch.int32))(bits)),
    }

def reference(x, qw_packed, scales, zeros, bits):
    b = int(bits)
    pf = 32 // b
    mask = (1 << b) - 1
    P, F = qw_packed.shape
    D = P * pf
    ng = scales.shape[0]
    G = D // ng
    shifts = (lambda x, dt: x.to(dt))(torch.arange(pf) * b, qw_packed.dtype)
    qw = ((qw_packed[:, None, :] >> shifts[None, :, None]) & mask).reshape(D, F)
    s = (lambda x, n, axis: torch.repeat_interleave(x, n, dim=axis))(scales, G, axis=0)
    z = (lambda x, n, axis: torch.repeat_interleave(x, n, dim=axis))(zeros, G, axis=0)
    w = ((lambda x, dt: x.to(dt))(qw, x.dtype) - z) * s
    return torch.einsum("bsd,df->bsf", x, w)
```

```cpp
#include <cuda.h>
#include <cuda_bf16.h>
#include <cuda_runtime.h>
#include <stdint.h>

namespace {

constexpr int kF = 4608;
constexpr int kSup = 512;
constexpr int kChunks = 9;
constexpr int kTiles = 4;
constexpr int kNX = 104;
constexpr int kClusters = 66;
#define EXTRA 60
constexpr int kExtraClusters = EXTRA;

#define STAGES 10
#define PRE 48
#define LAG0 1
#define LAG1 4
constexpr int kStages = STAGES;
constexpr int kStageBytes = 16384;
constexpr int kWPitch = 544;
constexpr int kOffOut = kStages * kStageBytes;
constexpr int kOffW = kOffOut + 2 * 16384;
constexpr int kOffZS = kOffW + 58 * kWPitch;
constexpr int kOffBar = kOffZS + 256;
constexpr int kBarFull = kOffBar;
constexpr int kBarEmpty = kBarFull + 8 * kStages;
constexpr int kBarW1 = kBarEmpty + 8 * kStages;
constexpr int kBarDq = kBarW1 + 8;
constexpr int kBarOutFull = kBarDq + 8;
constexpr int kBarOutFree = kBarOutFull + 16;
constexpr int kOffTrace = kBarOutFree + 16;
constexpr int kPre = PRE, kPer = (144 - kPre) / 8;
__host__ __device__ constexpr int last_word(int regs) { return (2 * regs - 1) / 5 > 56 ? 56 : (2 * regs - 1) / 5; }
constexpr int kFirst = last_word(kPre) / 8 + 1;
__host__ __device__ constexpr int need_step(int p) {
  int c = 0;
  while (c < 8 && last_word(kPre + (c + 1) * kPer) < 8 * p) ++c;
  return c;
}
#define PACE 300
constexpr int kSmemBytes = kOffTrace;
#define TR(role, idx)
#define TRALL(role, idx)
static_assert(kSmemBytes <= 232448, "smem");

__device__ __forceinline__ void mbar_init(uint32_t bar, uint32_t cnt) {
  asm volatile("mbarrier.init.shared::cta.b64 [%0], %1;" ::"r"(bar), "r"(cnt) : "memory");
}
__device__ __forceinline__ void mbar_expect_tx(uint32_t bar, uint32_t bytes) {
  asm volatile("mbarrier.arrive.expect_tx.shared::cta.b64 _, [%0], %1;" ::"r"(bar), "r"(bytes) : "memory");
}
__device__ __forceinline__ void mbar_arrive(uint32_t bar) {
  asm volatile("mbarrier.arrive.shared::cta.b64 _, [%0];" ::"r"(bar) : "memory");
}
__device__ __forceinline__ void mbar_wait(uint32_t bar, uint32_t parity) {
  asm volatile(
      "{\n.reg .pred p;\n.reg .u32 it;\n"
      "mbarrier.try_wait.parity.shared::cta.b64 p, [%0], %1;\n"
      "@p bra DONE;\n"
      "mov.u32 it, 0;\n"
      "SPIN:\n"
      "mbarrier.try_wait.parity.shared::cta.b64 p, [%0], %1;\n"
      "@p bra DONE;\n"
      "add.u32 it, it, 1;\n"
      "setp.lt.u32 p, it, 0x100000;\n"
      "@p bra SPIN;\n"
      "trap;\n"
      "DONE:\n}" ::"r"(bar),
      "r"(parity)
      : "memory");
}
__device__ __forceinline__ bool elect_one() {
  uint32_t p;
  asm volatile("{\n.reg .pred q;\nelect.sync _|q, 0xffffffff;\nselp.u32 %0, 1, 0, q;\n}" : "=r"(p));
  return p;
}
__device__ __forceinline__ void tma_load_2d(uint32_t dst, const CUtensorMap* tm, uint32_t bar, int c0, int c1) {
  asm volatile(
      "cp.async.bulk.tensor.2d.shared::cluster.global.mbarrier::complete_tx::bytes [%0], [%1, {%3, %4}], [%2];" ::"r"(dst),
      "l"(tm), "r"(bar), "r"(c0), "r"(c1)
      : "memory");
}
__device__ __forceinline__ void tma_load_2d_mc(uint32_t dst, const CUtensorMap* tm, uint32_t bar, int c0, int c1) {
  asm volatile(
      "cp.async.bulk.tensor.2d.shared::cluster.global.mbarrier::complete_tx::bytes.multicast::cluster [%0], [%1, {%3, "
      "%4}], [%2], %5;" ::"r"(dst),
      "l"(tm), "r"(bar), "r"(c0), "r"(c1), "h"((uint16_t)3)
      : "memory");
}
__device__ __forceinline__ void tma_prefetch_2d(const CUtensorMap* tm, int c0, int c1) {
  asm volatile("cp.async.bulk.prefetch.tensor.2d.L2.global [%0, {%1, %2}];" ::"l"(tm), "r"(c0), "r"(c1) : "memory");
}
__device__ __forceinline__ void bulk_load(uint32_t dst, const void* src, uint32_t bytes, uint32_t bar) {
  asm volatile("cp.async.bulk.shared::cluster.global.mbarrier::complete_tx::bytes [%0], [%1], %2, [%3];" ::"r"(dst),
               "l"(src), "r"(bytes), "r"(bar)
               : "memory");
}
__device__ __forceinline__ void tma_store_2d(const CUtensorMap* tm, uint32_t src, int c0, int c1) {
  asm volatile("cp.async.bulk.tensor.2d.global.shared::cta.bulk_group [%0, {%2, %3}], [%1];" ::"l"(tm), "r"(src),
               "r"(c0), "r"(c1)
               : "memory");
}
__device__ __forceinline__ void wgmma_fence() { asm volatile("wgmma.fence.sync.aligned;" ::: "memory"); }
__device__ __forceinline__ void wgmma_commit() { asm volatile("wgmma.commit_group.sync.aligned;" ::: "memory"); }
template <int N>
__device__ __forceinline__ void wgmma_wait() {
  asm volatile("wgmma.wait_group.sync.aligned %0;" ::"n"(N) : "memory");
}
__device__ __forceinline__ uint64_t smem_desc(uint32_t addr) {
  return (uint64_t)((addr & 0x3FFFF) >> 4) | (1ull << 16) | (64ull << 32) | (1ull << 62);
}
__device__ __forceinline__ uint32_t bf16x2_fma(uint32_t a, uint32_t b, uint32_t c) {
  uint32_t d;
  asm("fma.rn.bf16x2 %0, %1, %2, %3;" : "=r"(d) : "r"(a), "r"(b), "r"(c));
  return d;
}
__device__ __forceinline__ uint32_t bf16x2_mul(uint32_t a, uint32_t b) {
  uint32_t d;
  asm("mul.rn.bf16x2 %0, %1, %2;" : "=r"(d) : "r"(a), "r"(b));
  return d;
}

template <int ACC>
__device__ __forceinline__ void wgmma_rs_n128(float (&d)[64], uint32_t a0, uint32_t a1, uint32_t a2, uint32_t a3,
                                              uint64_t desc_b) {
  asm volatile(
      "{\n.reg .pred p;\nsetp.ne.b32 p, %69, 0;\n"
      "wgmma.mma_async.sync.aligned.m64n128k16.f32.bf16.bf16 {"
      "%0, %1, %2, %3, %4, %5, %6, %7, %8, %9, %10, %11, %12, %13, %14, %15, "
      "%16, %17, %18, %19, %20, %21, %22, %23, %24, %25, %26, %27, %28, %29, %30, %31, "
      "%32, %33, %34, %35, %36, %37, %38, %39, %40, %41, %42, %43, %44, %45, %46, %47, "
      "%48, %49, %50, %51, %52, %53, %54, %55, %56, %57, %58, %59, %60, %61, %62, %63"
      "}, {%64, %65, %66, %67}, %68, p, 1, 1, 0;\n}\n"
      : "+f"(d[0]), "+f"(d[1]), "+f"(d[2]), "+f"(d[3]), "+f"(d[4]), "+f"(d[5]), "+f"(d[6]), "+f"(d[7]),
        "+f"(d[8]), "+f"(d[9]), "+f"(d[10]), "+f"(d[11]), "+f"(d[12]), "+f"(d[13]), "+f"(d[14]), "+f"(d[15]),
        "+f"(d[16]), "+f"(d[17]), "+f"(d[18]), "+f"(d[19]), "+f"(d[20]), "+f"(d[21]), "+f"(d[22]), "+f"(d[23]),
        "+f"(d[24]), "+f"(d[25]), "+f"(d[26]), "+f"(d[27]), "+f"(d[28]), "+f"(d[29]), "+f"(d[30]), "+f"(d[31]),
        "+f"(d[32]), "+f"(d[33]), "+f"(d[34]), "+f"(d[35]), "+f"(d[36]), "+f"(d[37]), "+f"(d[38]), "+f"(d[39]),
        "+f"(d[40]), "+f"(d[41]), "+f"(d[42]), "+f"(d[43]), "+f"(d[44]), "+f"(d[45]), "+f"(d[46]), "+f"(d[47]),
        "+f"(d[48]), "+f"(d[49]), "+f"(d[50]), "+f"(d[51]), "+f"(d[52]), "+f"(d[53]), "+f"(d[54]), "+f"(d[55]),
        "+f"(d[56]), "+f"(d[57]), "+f"(d[58]), "+f"(d[59]), "+f"(d[60]), "+f"(d[61]), "+f"(d[62]), "+f"(d[63])
      : "r"(a0), "r"(a1), "r"(a2), "r"(a3), "l"(desc_b), "n"(ACC));
}

template <int ACC>
__device__ __forceinline__ void wgmma_rs_n104(float (&d)[64], uint32_t a0, uint32_t a1, uint32_t a2, uint32_t a3,
                                              uint64_t desc_b) {
  asm volatile(
      "{\n.reg .pred p;\nsetp.ne.b32 p, %57, 0;\n"
      "wgmma.mma_async.sync.aligned.m64n104k16.f32.bf16.bf16 {"
      "%0, %1, %2, %3, %4, %5, %6, %7, %8, %9, %10, %11, %12, %13, %14, %15, "
      "%16, %17, %18, %19, %20, %21, %22, %23, %24, %25, %26, %27, %28, %29, %30, %31, "
      "%32, %33, %34, %35, %36, %37, %38, %39, %40, %41, %42, %43, %44, %45, %46, %47, "
      "%48, %49, %50, %51"
      "}, {%52, %53, %54, %55}, %56, p, 1, 1, 0;\n}\n"
      : "+f"(d[0]), "+f"(d[1]), "+f"(d[2]), "+f"(d[3]), "+f"(d[4]), "+f"(d[5]), "+f"(d[6]), "+f"(d[7]),
        "+f"(d[8]), "+f"(d[9]), "+f"(d[10]), "+f"(d[11]), "+f"(d[12]), "+f"(d[13]), "+f"(d[14]), "+f"(d[15]),
        "+f"(d[16]), "+f"(d[17]), "+f"(d[18]), "+f"(d[19]), "+f"(d[20]), "+f"(d[21]), "+f"(d[22]), "+f"(d[23]),
        "+f"(d[24]), "+f"(d[25]), "+f"(d[26]), "+f"(d[27]), "+f"(d[28]), "+f"(d[29]), "+f"(d[30]), "+f"(d[31]),
        "+f"(d[32]), "+f"(d[33]), "+f"(d[34]), "+f"(d[35]), "+f"(d[36]), "+f"(d[37]), "+f"(d[38]), "+f"(d[39]),
        "+f"(d[40]), "+f"(d[41]), "+f"(d[42]), "+f"(d[43]), "+f"(d[44]), "+f"(d[45]), "+f"(d[46]), "+f"(d[47]),
        "+f"(d[48]), "+f"(d[49]), "+f"(d[50]), "+f"(d[51])
      : "r"(a0), "r"(a1), "r"(a2), "r"(a3), "l"(desc_b), "n"(ACC));
}

struct Ring {
  uint32_t stage, parity;
  __device__ __forceinline__ void next() {
    if (++stage == kStages) { stage = 0; parity ^= 1; }
  }
};

#define IMASK 10
__host__ __device__ constexpr bool use_imad(int b) { return (IMASK >> b) & 1; }
struct Dq {
  uint32_t addr[5], sh[5];
  uint32_t c[2], s[2];
  int tj;
};

__device__ __forceinline__ void dq_setup(Dq& q, uint32_t sb, int col, int phase) {
  const int lane = threadIdx.x & 31;
  q.tj = (lane & 3) - phase;
  const uint32_t base = sb + kOffW + col * 4;
#pragma unroll
  for (int b = 0; b < 5; ++b) {
    const int e = 4 * b + q.tj + 5;
    const int o = (e * 52) >> 8;
    q.addr[b] = base + (o - 1) * kWPitch;
    q.sh[b] = use_imad(b) ? 1u << (24 - 6 * (e - 5 * o)) : 6 * (e - 5 * o);
  }
}
__device__ __forceinline__ void dq_consts(Dq& q, int h, uint16_t z, uint16_t s) {
  q.c[h] = bf16x2_mul((uint32_t)z * 0x10001u, 0xBE00BC80u);
  q.s[h] = bf16x2_mul((uint32_t)s * 0x10001u, 0x41004280u);
}
template <int R0, int NR>
__device__ __forceinline__ void dq_regs(uint32_t (&a)[144], const Dq& q) {
#pragma unroll
  for (int i = R0; i < R0 + NR; ++i) {
    const int u = i >> 1, h = i & 1;
    uint32_t w;
    asm volatile("ld.shared.u32 %0, [%1];" : "=r"(w) : "r"(q.addr[u % 5] + (u / 5) * 4 * kWPitch + h * 32));
    if (use_imad(u % 5)) w = __byte_perm(w * q.sh[u % 5], 0, 0x3333);
    else w = __byte_perm(w >> q.sh[u % 5], 0, 0x0000);
    w &= 0x00380007u;
    w = bf16x2_mul(bf16x2_fma(w, 0x7F007F00u, q.c[h]), q.s[h]);
    if (u == 0) w = q.tj < 0 ? 0u : w;
    if (u == 71) w = q.tj > 0 ? 0u : w;
    a[i] = w;
  }
}

template <int N, int C>
__device__ __forceinline__ void mma_chunk(float (&d)[64], const uint32_t (&a)[144], uint64_t desc) {
  wgmma_fence();
#pragma unroll
  for (int s = 4 * C; s < 4 * C + 4; ++s) {
    if (N == 128) {
      if (s == 0) wgmma_rs_n128<0>(d, a[0], a[1], a[2], a[3], desc);
      else wgmma_rs_n128<1>(d, a[4 * s], a[4 * s + 1], a[4 * s + 2], a[4 * s + 3], desc + 2 * (s & 3));
    } else {
      if (s == 0) wgmma_rs_n104<0>(d, a[0], a[1], a[2], a[3], desc);
      else wgmma_rs_n104<1>(d, a[4 * s], a[4 * s + 1], a[4 * s + 2], a[4 * s + 3], desc + 2 * (s & 3));
    }
  }
  wgmma_commit();
}

#define BOUNDARY(I)
#define BOUNDARY2(I)
struct Ctx {
  uint32_t sb;
  uint32_t empty_dst;
  int wg;
  int rel_left;
};

__device__ __forceinline__ void release(Ctx& cx, uint32_t stage) {
  if (cx.rel_left > 0 && (threadIdx.x & 31) < 2)
    asm volatile("mbarrier.arrive.shared::cluster.b64 _, [%0];" ::"r"(cx.empty_dst + stage * 8) : "memory");
  --cx.rel_left;
}

__device__ __forceinline__ void wg_sync(int wg) {
  if (wg == 0) asm volatile("bar.sync 3, 128;" ::: "memory");
  else asm volatile("bar.sync 4, 128;" ::: "memory");
}

template <int MODE, int C>
__device__ __forceinline__ void tile_step(float (&d)[64], uint32_t (&a)[144], const Dq& q, Ctx& cx, Ring& ring,
                                          uint32_t& prev, int lag, int trbase) {
  const uint32_t sb = cx.sb;
  mbar_wait(sb + kBarFull + ring.stage * 8, ring.parity);
  if (MODE != 3 && C == 0 && cx.wg == 1) asm volatile("bar.sync 1, 256;" ::: "memory");
  TR(cx.wg, trbase + C);
  mma_chunk<MODE == 3 ? kNX : 128, C>(d, a, smem_desc(sb + ring.stage * kStageBytes));
  if (MODE != 3 && lag == C && cx.wg == 0) asm volatile("bar.arrive 1, 256;" ::: "memory");
  if (MODE == 1) {
    BOUNDARY(C);
    if (C < 8 && kPer > 0) dq_regs<(kPre + C * kPer) % 144, kPer>(a, q);
  }
  if (MODE == 3 && C < 2) {
    BOUNDARY(20 + C);
    dq_regs<16 * (7 + C), 16>(a, q);
  }
  if (MODE == 2) {
    if (C >= 2) {
      wgmma_wait<2>();
      BOUNDARY2(30 + C);
      dq_regs<16 * ((C + 7) % 9), 16>(a, q);
    }
    if (C >= 1) {
      wgmma_wait<1>();
      release(cx, prev);
    }
  } else if (C > 0 && MODE != 3) {
    wgmma_wait<1>();
    release(cx, prev);
  }
  prev = ring.stage;
  ring.next();
}

template <int MODE>
__device__ __forceinline__ void tile(float (&d)[64], uint32_t (&a)[144], const Dq& q, Ctx& cx, Ring& ring, int lag,
                                     uint32_t out_parity, int trbase) {
  constexpr int N = MODE == 3 ? kNX : 128;
  const uint32_t sb = cx.sb;
  uint32_t prev = 0;
  tile_step<MODE, 0>(d, a, q, cx, ring, prev, lag, trbase);
  tile_step<MODE, 1>(d, a, q, cx, ring, prev, lag, trbase);
  tile_step<MODE, 2>(d, a, q, cx, ring, prev, lag, trbase);
  tile_step<MODE, 3>(d, a, q, cx, ring, prev, lag, trbase);
  tile_step<MODE, 4>(d, a, q, cx, ring, prev, lag, trbase);
  tile_step<MODE, 5>(d, a, q, cx, ring, prev, lag, trbase);
  tile_step<MODE, 6>(d, a, q, cx, ring, prev, lag, trbase);
  tile_step<MODE, 7>(d, a, q, cx, ring, prev, lag, trbase);
  tile_step<MODE, 8>(d, a, q, cx, ring, prev, lag, trbase);
  const int lane = threadIdx.x & 31, warp = (threadIdx.x >> 5) & 3;
  if (MODE == 1 && lane == 0) mbar_arrive(sb + kBarDq);
  if (MODE != 1) mbar_wait(sb + kBarOutFree + cx.wg * 8, out_parity);
  wgmma_wait<0>();
#pragma unroll
  for (int i = 0; i < N / 2; ++i) asm volatile("" : "+f"(d[i])::"memory");
  if (MODE != 3) release(cx, prev);
  TR(cx.wg, trbase + 9);
  const uint32_t st = sb + kOffOut + cx.wg * 16384 + ((lane & 7) + ((lane >> 4) << 3)) * 128 +
                      (((warp * 2 + ((lane >> 3) & 1)) ^ (lane & 7)) << 4);
#pragma unroll
  for (int i = 0; i < N / 8; i += 2) {
    uint32_t r0, r1, r2, r3;
    asm("cvt.rn.bf16x2.f32 %0, %1, %2;" : "=r"(r0) : "f"(d[4 * i + 1]), "f"(d[4 * i]));
    asm("cvt.rn.bf16x2.f32 %0, %1, %2;" : "=r"(r1) : "f"(d[4 * i + 3]), "f"(d[4 * i + 2]));
    if (i + 1 < N / 8) {
      asm("cvt.rn.bf16x2.f32 %0, %1, %2;" : "=r"(r2) : "f"(d[4 * i + 5]), "f"(d[4 * i + 4]));
      asm("cvt.rn.bf16x2.f32 %0, %1, %2;" : "=r"(r3) : "f"(d[4 * i + 7]), "f"(d[4 * i + 6]));
      asm volatile("stmatrix.sync.aligned.m8n8.x4.trans.shared.b16 [%0], {%1, %2, %3, %4};" ::"r"(st + i * 1024),
                   "r"(r0), "r"(r1), "r"(r2), "r"(r3)
                   : "memory");
    } else {
      asm volatile("stmatrix.sync.aligned.m8n8.x2.trans.shared.b16 [%0], {%1, %2};" ::"r"(st + i * 1024), "r"(r0),
                   "r"(r1)
                   : "memory");
    }
  }
  asm volatile("fence.proxy.async.shared::cta;" ::: "memory");
  __syncwarp();
  if (lane == 0) mbar_arrive(sb + kBarOutFull + cx.wg * 8);
  if (trbase != 44) TR(cx.wg, trbase + 10);
}

__global__ void __cluster_dims__(2, 1, 1) __launch_bounds__(384, 1)
    gptq_gemm_kernel(const uint32_t* __restrict__ qw, const __nv_bfloat16* __restrict__ scales,
                     const __nv_bfloat16* __restrict__ zeros, const __grid_constant__ CUtensorMap tm_x64,
                     const __grid_constant__ CUtensorMap tm_w, const __grid_constant__ CUtensorMap tm_o128,
                     const __grid_constant__ CUtensorMap tm_x52, const __grid_constant__ CUtensorMap tm_o104) {
  extern __shared__ __align__(1024) uint8_t smem[];
  const uint32_t sb = (uint32_t)__cvta_generic_to_shared(smem);
  const int cid = blockIdx.x >> 1, rank = blockIdx.x & 1;
  const int phase = cid & 3, n_own = (cid >> 2) * 256 + rank * 128;
  const int rot = 0;
  const int warp_id = __shfl_sync(0xffffffffu, (int)(threadIdx.x >> 5), 0);
  const int wg = warp_id >> 2;
  const int lane = threadIdx.x & 31;
  const int col = warp_id * 16 + (lane >> 2);
  uint16_t z0, z1, s0, s1;
  uint32_t t0;

  if ((threadIdx.x >> 5) != 8) asm volatile("barrier.cluster.arrive.relaxed.aligned;" ::: "memory");
  if (warp_id < 8) {
    const int tid = threadIdx.x & 127;
    const uint32_t* src = qw + ((tid >> 4) * kF + n_own + wg * 64 + (tid & 15) * 4);
    const uint32_t dst = sb + kOffW + (tid >> 4) * kWPitch + wg * 256 + (tid & 15) * 16;
#pragma unroll
    for (int i = 0; i < kFirst; ++i) {
      if (i < 7 || tid < 16)
        asm volatile("cp.async.cg.shared.global [%0], [%1], 16;" ::"r"(dst + i * 8 * kWPitch), "l"(src + i * 8 * kF)
                     : "memory");
      if (i == 0) {
        asm volatile("cp.async.commit_group;" ::: "memory");
        TR(wg, 59);
        const uint16_t* zp = reinterpret_cast<const uint16_t*>(zeros) + (n_own + col);
        const uint16_t* sp = reinterpret_cast<const uint16_t*>(scales) + (n_own + col);
        asm volatile("ld.global.nc.u16 %0, [%1];" : "=h"(z0) : "l"(zp));
        asm volatile("ld.global.nc.u16 %0, [%1+16];" : "=h"(z1) : "l"(zp));
        asm volatile("ld.global.nc.u16 %0, [%1];" : "=h"(s0) : "l"(sp));
        asm volatile("ld.global.nc.u16 %0, [%1+16];" : "=h"(s1) : "l"(sp));
      }
    }
    asm volatile("cp.async.commit_group;" ::: "memory");
  }

  const bool has_extra = cid < kExtraClusters;
  const int ue = kClusters + cid / 10;
  const int phase_e = ue & 3, n_e = (ue >> 2) * 256 + ((cid / 5) & 1) * 128 + rank * 64, row_e = (cid % 5) * kNX;
  const int total = has_extra ? 5 * kChunks : 4 * kChunks;

  if (wg == 2) {
    asm volatile("setmaxnreg.dec.sync.aligned.u32 24;");
    if (warp_id == 8) {
      const bool leader = elect_one();
      if (leader) {
        TRALL(2, 56);
#pragma unroll
        for (int i = 0; i < kStages; ++i) mbar_init(sb + kBarFull + 8 * i, 1);
        asm volatile("fence.mbarrier_init.release.cluster;" ::: "memory");
        TRALL(2, 57);
      }
      __syncwarp();
      asm volatile("barrier.cluster.arrive.relaxed.aligned;" ::: "memory");
      asm volatile("barrier.cluster.wait.aligned;" ::: "memory");
      if (leader) {
        TRALL(2, 59);
        uint32_t bytes = kStageBytes;
#pragma unroll
        for (int p = kFirst; p < 8; ++p)
          if (need_step(p) == 0) bytes += 8 * kWPitch;
        mbar_expect_tx(sb + kBarFull, bytes);
        tma_load_2d_mc(sb + rank * 8192, &tm_x64, sb + kBarFull, phase * 568, rank * 64 + rot * 128);
#pragma unroll
        for (int p = kFirst; p < 8; ++p)
          if (need_step(p) == 0) tma_load_2d(sb + kOffW + p * 8 * kWPitch, &tm_w, sb + kBarFull, n_own, p * 8);
        TRALL(2, 0);
#pragma unroll
        for (int i = 0; i < kStages; ++i) mbar_init(sb + kBarEmpty + 8 * i, 16);
        mbar_init(sb + kBarW1, 1);
        mbar_init(sb + kBarDq, 8);
        mbar_init(sb + kBarOutFull, 4);
        mbar_init(sb + kBarOutFull + 8, 4);
        mbar_init(sb + kBarOutFree, 1);
        mbar_init(sb + kBarOutFree + 8, 1);
        asm volatile("fence.mbarrier_init.release.cluster;" ::: "memory");
      }
      asm volatile("mov.u32 %0, %clock;" : "=r"(t0));
      __syncwarp();
      asm volatile("bar.arrive 2, 288;" ::: "memory");
      asm volatile("bar.arrive 5, 96;" ::: "memory");
      if (leader) {
#pragma unroll
        for (int g = 1; g < kStages; ++g) {
          const uint32_t full = sb + kBarFull + g * 8;
          if (g > 0 && PACE > 0) {
            uint32_t t;
            do { asm volatile("mov.u32 %0, %clock;" : "=r"(t)); } while (t - t0 < g * PACE);
          }
          TRALL(2, g);
          uint32_t bytes = kStageBytes;
#pragma unroll
          for (int p = kFirst; p < 8; ++p)
            if (need_step(p) == g) bytes += p < 7 ? 8 * kWPitch : 512;
          mbar_expect_tx(full, bytes);
          tma_load_2d_mc(sb + g * kStageBytes + rank * 8192, &tm_x64, full, phase * 568 + (g % kChunks) * 64,
                         rank * 64 + ((g / kChunks + rot) & 3) * 128);
#pragma unroll
          for (int p = kFirst; p < 8; ++p)
            if (need_step(p) == g) {
              if (p < 7) tma_load_2d(sb + kOffW + p * 8 * kWPitch, &tm_w, full, n_own, p * 8);
              else bulk_load(sb + kOffW + 56 * kWPitch, qw + 56 * kF + n_own, 512, full);
            }
        }
        Ring ring{0, 0};
        int c = kStages % kChunks, row = rank * 64 + ((kStages / kChunks + rot) & 3) * 128;
#pragma unroll 1
        for (int g = kStages; g < total; ++g) {
          const uint32_t full = sb + kBarFull + ring.stage * 8;
          mbar_wait(sb + kBarEmpty + ring.stage * 8, ring.parity);
          TRALL(2, g);
          const uint32_t dst = sb + ring.stage * kStageBytes;
          if (g < 4 * kChunks) {
            mbar_expect_tx(full, kStageBytes);
            tma_load_2d_mc(dst + rank * 8192, &tm_x64, full, phase * 568 + c * 64, row);
          } else {
            mbar_expect_tx(full, kNX * 128);
            tma_load_2d_mc(dst + rank * (kNX * 64), &tm_x52, full, phase_e * 568 + c * 64, row_e + rank * (kNX / 2));
          }
          if (++c == kChunks) { c = 0; row = (row + 128) & 511; }
          ring.next();
        }
      }
    } else if (warp_id < 11) {
      if (warp_id == 10) {
        asm volatile("prefetch.tensormap [%0];" ::"l"(&tm_x64) : "memory");
        asm volatile("prefetch.tensormap [%0];" ::"l"(&tm_w) : "memory");
      }
      asm volatile("bar.sync 5, 96;" ::: "memory");
      const int w = warp_id - 9;
      if (elect_one()) {
        const int nst = (has_extra && w == 0) ? 5 : 4;
#pragma unroll 1
        for (int t = 0; t < nst; ++t) {
          if (t == 0 && w == 0) {
            mbar_wait(sb + kBarFull + 24, 0);
            asm volatile("prefetch.tensormap [%0];" ::"l"(&tm_o128) : "memory");
          }
          mbar_wait(sb + kBarOutFull + w * 8, t & 1);
          TRALL(3, 4 * t + 2 * w);
          if (t < 4) tma_store_2d(&tm_o128, sb + kOffOut + w * 16384, phase * kF + n_own + w * 64, ((t + rot) & 3) * 128);
          else tma_store_2d(&tm_o104, sb + kOffOut, phase_e * kF + n_e, row_e);
          asm volatile("cp.async.bulk.commit_group;" ::: "memory");
          if (t == 0 && w == 1 && has_extra) {
            mbar_wait(sb + kBarDq, 0);
            mbar_expect_tx(sb + kBarW1, 56 * kWPitch + 256 + 256);
            bulk_load(sb + kOffZS, zeros + n_e, 128, sb + kBarW1);
            bulk_load(sb + kOffZS + 128, scales + n_e, 128, sb + kBarW1);
            bulk_load(sb + kOffW + 56 * kWPitch, qw + 56 * kF + n_e, 256, sb + kBarW1);
#pragma unroll 1
            for (int p = 0; p < 7; ++p) {
              tma_load_2d(sb + kOffW + p * 8 * kWPitch, &tm_w, sb + kBarW1, n_e, p * 8);
              __nanosleep(200);
            }
            asm volatile("prefetch.tensormap [%0];" ::"l"(&tm_x52) : "memory");
            asm volatile("prefetch.tensormap [%0];" ::"l"(&tm_o104) : "memory");
          }
          asm volatile("cp.async.bulk.wait_group.read 0;" ::: "memory");
          mbar_arrive(sb + kBarOutFree + w * 8);
          TRALL(3, 4 * t + 2 * w + 1);
        }
      }
    }
  } else {
    TR(wg, 54);
    asm volatile("setmaxnreg.inc.sync.aligned.u32 240;");
    Ctx cx;
    cx.sb = sb;
    cx.wg = wg;
    cx.rel_left = total - kStages;
    asm("mapa.shared::cluster.u32 %0, %1, %2;" : "=r"(cx.empty_dst) : "r"(sb + kBarEmpty), "r"(lane & 1));
    float d[64];
    uint32_t a[144];
    Dq q;
    Ring ring{0, 0};
    dq_setup(q, sb, col, phase);
    dq_consts(q, 0, z0, s0);
    dq_consts(q, 1, z1, s1);
    asm volatile("cp.async.wait_group 1;" ::: "memory");
    wg_sync(wg);
    TR(wg, 58);
    dq_regs<0, 16>(a, q);
    if (kPre > 16) {
      asm volatile("cp.async.wait_group 0;" ::: "memory");
      wg_sync(wg);
      TR(wg, 57);
      dq_regs<16, kPre - 16>(a, q);
    }
    TR(wg, 56);
    asm volatile("bar.sync 2, 288;" ::: "memory");
    TR(wg, 55);
    tile<1>(d, a, q, cx, ring, LAG0, 0, 0);
    const bool extra = wg == 0 && has_extra;
    const int nplain = extra ? 3 : 4;
#pragma unroll 1
    for (int t = 1; t < nplain; ++t) tile<0>(d, a, q, cx, ring, LAG1, (t - 1) & 1, t * 11);
    if (extra) {
      const int cole = (warp_id & 3) * 16 + (lane >> 2);
      dq_setup(q, sb, cole, phase_e);
      mbar_wait(sb + kBarW1, 0);
#pragma unroll
      for (int h = 0; h < 2; ++h) {
        uint16_t z, s;
        asm volatile("ld.shared.u16 %0, [%1];" : "=h"(z) : "r"(sb + kOffZS + (cole + 8 * h) * 2));
        asm volatile("ld.shared.u16 %0, [%1];" : "=h"(s) : "r"(sb + kOffZS + 128 + (cole + 8 * h) * 2));
        dq_consts(q, h, z, s);
      }
      tile<2>(d, a, q, cx, ring, LAG1, 0, 33);
      tile<3>(d, a, q, cx, ring, -1, 1, 44);
    }
  }
}

typedef CUresult (*EncodeFn)(CUtensorMap*, CUtensorMapDataType, cuuint32_t, void*, const cuuint64_t*,
                             const cuuint64_t*, const cuuint32_t*, const cuuint32_t*, CUtensorMapInterleave,
                             CUtensorMapSwizzle, CUtensorMapL2promotion, CUtensorMapFloatOOBfill);

void make_map(EncodeFn enc, CUtensorMap* tm, CUtensorMapDataType dt, const void* base, uint64_t d0, uint64_t d1,
              uint64_t stride, uint32_t b0, uint32_t b1, CUtensorMapSwizzle sw, CUtensorMapL2promotion promo) {
  cuuint64_t dims[2] = {d0, d1};
  cuuint64_t strides[1] = {stride};
  cuuint32_t box[2] = {b0, b1};
  cuuint32_t es[2] = {1, 1};
  enc(tm, dt, 2, const_cast<void*>(base), dims, strides, box, es, CU_TENSOR_MAP_INTERLEAVE_NONE, sw, promo,
      CU_TENSOR_MAP_FLOAT_OOB_FILL_NONE);
}

}

extern "C" void kernel_launch(void* const* d_in, const int* in_sizes, int n_in, void* d_out, int out_size) {
  (void)in_sizes; (void)n_in; (void)out_size;
  static EncodeFn enc = nullptr;
  if (!enc) {
    void* fn = nullptr;
    cudaDriverEntryPointQueryResult qr;
    cudaGetDriverEntryPoint("cuTensorMapEncodeTiled", &fn, cudaEnableDefault, &qr);
    enc = (EncodeFn)fn;
    cudaFuncSetAttribute(gptq_gemm_kernel, cudaFuncAttributeMaxDynamicSharedMemorySize, kSmemBytes);
  }
  CUtensorMap x64, x52, w, o128, o104;
  make_map(enc, &x64, CU_TENSOR_MAP_DATA_TYPE_BFLOAT16, d_in[0], 2280, kSup, 4560, 64, 64, CU_TENSOR_MAP_SWIZZLE_128B,
           CU_TENSOR_MAP_L2_PROMOTION_L2_128B);
  make_map(enc, &x52, CU_TENSOR_MAP_DATA_TYPE_BFLOAT16, d_in[0], 2280, kSup, 4560, 64, kNX / 2,
           CU_TENSOR_MAP_SWIZZLE_128B, CU_TENSOR_MAP_L2_PROMOTION_L2_128B);
  make_map(enc, &w, CU_TENSOR_MAP_DATA_TYPE_INT32, d_in[1], kF, 57, kF * 4, 136, 8, CU_TENSOR_MAP_SWIZZLE_NONE,
           CU_TENSOR_MAP_L2_PROMOTION_L2_128B);
  make_map(enc, &o128, CU_TENSOR_MAP_DATA_TYPE_BFLOAT16, d_out, 4 * kF, kSup, 8 * kF, 64, 128,
           CU_TENSOR_MAP_SWIZZLE_128B, CU_TENSOR_MAP_L2_PROMOTION_NONE);
  make_map(enc, &o104, CU_TENSOR_MAP_DATA_TYPE_BFLOAT16, d_out, 4 * kF, kSup, 8 * kF, 64, kNX,
           CU_TENSOR_MAP_SWIZZLE_128B, CU_TENSOR_MAP_L2_PROMOTION_NONE);
  gptq_gemm_kernel<<<2 * kClusters, 384, kSmemBytes>>>(
      (const uint32_t*)d_in[1], (const __nv_bfloat16*)d_in[2], (const __nv_bfloat16*)d_in[3], x64, w, o128, x52, o104);
}
```

```cpp
#include <cuda.h>
#include <cuda_bf16.h>
#include <cuda_runtime.h>
#include <stdint.h>

namespace {

constexpr int kF = 4608;
constexpr int kSup = 512;
constexpr int kChunks = 9;
constexpr int kNX = 104;
constexpr int kClusters = 66;
constexpr int kExtraClusters = 60;

#define LAZY 4000
#define PRE 48
#define LAG0 1
#define LAG1 4
#define LAG3 LAG1
#define GATE 6
#define PACE 400
#define IMASK 10
#define KSS 2
#define STAGES 10
constexpr int kStages = STAGES;
constexpr int kStageBytes = 16384;
constexpr int kWPitch = 544;
constexpr int kWePitch = 288;
constexpr int kSS = KSS;
constexpr int kHeadRows = (64 * kSS + 9) / 10;
constexpr int kWeRow0 = (32 * kSS - 3) / 5;
constexpr int kWeRows = 57 - kWeRow0;
constexpr int kOffOut = kStages * kStageBytes;
constexpr int kOffW = kOffOut + 2 * 16384;
constexpr int kOffAx = kOffW;
constexpr int kOffWe = kOffAx + (10 * kHeadRows + 6) * 128;
constexpr int kOffHead = kOffWe + (kWeRows + 1) * kWePitch;
constexpr int kOffZS = kOffHead + kHeadRows * 256;
constexpr int kOffBar = kOffZS + 256 > kOffW + 58 * kWPitch ? kOffZS + 256 : kOffW + 58 * kWPitch;
constexpr int kBarFull = kOffBar;
constexpr int kBarEmpty = kBarFull + 8 * kStages;
constexpr int kBarW1 = kBarEmpty + 8 * kStages;
constexpr int kBarDq = kBarW1 + 8;
constexpr int kBarAx = kBarDq + 8;
constexpr int kBarLd = kBarAx + 8;
constexpr int kBarOutFull = kBarLd + 8;
constexpr int kBarOutFree = kBarOutFull + 16;
constexpr int kOffTrace = kBarOutFree + 16;

constexpr int kPre = PRE, kPer = (144 - kPre) / 8;
__host__ __device__ constexpr int last_word(int regs) { return (2 * regs - 1) / 5 > 56 ? 56 : (2 * regs - 1) / 5; }
#define SPLIT1 1
constexpr int kFirst = last_word(kPre + (1 + SPLIT1) * kPer) / 8 + 1;
__host__ __device__ constexpr int need_step(int p) {
  int c = 0;
  while (c < 8 && last_word(kPre + (c + 1 + SPLIT1) * kPer) < 8 * p) ++c;
  return c;
}
__host__ __device__ constexpr int trail_end(int c) {
  return c < 2 ? 0 : ((16 * (kChunks - kSS) * (c - 1) + 13) / 14) * 2 > 16 * (kChunks - kSS)
                         ? 16 * (kChunks - kSS)
                         : ((16 * (kChunks - kSS) * (c - 1) + 13) / 14) * 2;
}

constexpr int kSmemBytes = kOffTrace;
#define TR(role, idx)
#define TRALL(role, idx)
static_assert(kSmemBytes <= 232448, "smem");
static_assert(kFirst <= 7 && kStages >= kChunks, "config");

__device__ __forceinline__ void mbar_init(uint32_t bar, uint32_t cnt) {
  asm volatile("mbarrier.init.shared::cta.b64 [%0], %1;" ::"r"(bar), "r"(cnt) : "memory");
}
__device__ __forceinline__ void mbar_expect_tx(uint32_t bar, uint32_t bytes) {
  asm volatile("mbarrier.arrive.expect_tx.shared::cta.b64 _, [%0], %1;" ::"r"(bar), "r"(bytes) : "memory");
}
__device__ __forceinline__ void mbar_arrive(uint32_t bar) {
  asm volatile("mbarrier.arrive.shared::cta.b64 _, [%0];" ::"r"(bar) : "memory");
}
__device__ __forceinline__ void mbar_wait(uint32_t bar, uint32_t parity) {
  asm volatile(
      "{\n.reg .pred p;\n.reg .u32 it;\n"
      "mbarrier.try_wait.parity.shared::cta.b64 p, [%0], %1;\n"
      "@p bra DONE;\n"
      "mov.u32 it, 0;\n"
      "SPIN:\n"
      "mbarrier.try_wait.parity.shared::cta.b64 p, [%0], %1;\n"
      "@p bra DONE;\n"
      "add.u32 it, it, 1;\n"
      "setp.lt.u32 p, it, 0x100000;\n"
      "@p bra SPIN;\n"
      "trap;\n"
      "DONE:\n}" ::"r"(bar),
      "r"(parity)
      : "memory");
}
__device__ __forceinline__ void mbar_wait_lazy(uint32_t bar, uint32_t parity) {
  asm volatile(
      "{\n.reg .pred p;\n.reg .u32 it;\n"
      "mov.u32 it, 0;\n"
      "SPIN:\n"
      "mbarrier.try_wait.parity.shared::cta.b64 p, [%0], %1, %2;\n"
      "@p bra DONE;\n"
      "add.u32 it, it, 1;\n"
      "setp.lt.u32 p, it, 0x40000;\n"
      "@p bra SPIN;\n"
      "trap;\n"
      "DONE:\n}" ::"r"(bar),
      "r"(parity), "r"(LAZY)
      : "memory");
}
__device__ __forceinline__ bool elect_one() {
  uint32_t p;
  asm volatile("{\n.reg .pred q;\nelect.sync _|q, 0xffffffff;\nselp.u32 %0, 1, 0, q;\n}" : "=r"(p));
  return p;
}
__device__ __forceinline__ void tma_load_2d(uint32_t dst, const CUtensorMap* tm, uint32_t bar, int c0, int c1) {
  asm volatile(
      "cp.async.bulk.tensor.2d.shared::cluster.global.mbarrier::complete_tx::bytes [%0], [%1, {%3, %4}], [%2];" ::"r"(dst),
      "l"(tm), "r"(bar), "r"(c0), "r"(c1)
      : "memory");
}
__device__ __forceinline__ void tma_load_2d_mc(uint32_t dst, const CUtensorMap* tm, uint32_t bar, int c0, int c1) {
  asm volatile(
      "cp.async.bulk.tensor.2d.shared::cluster.global.mbarrier::complete_tx::bytes.multicast::cluster [%0], [%1, {%3, "
      "%4}], [%2], %5;" ::"r"(dst),
      "l"(tm), "r"(bar), "r"(c0), "r"(c1), "h"((uint16_t)3)
      : "memory");
}
__device__ __forceinline__ void bulk_load(uint32_t dst, const void* src, uint32_t bytes, uint32_t bar) {
  asm volatile("cp.async.bulk.shared::cluster.global.mbarrier::complete_tx::bytes [%0], [%1], %2, [%3];" ::"r"(dst),
               "l"(src), "r"(bytes), "r"(bar)
               : "memory");
}
__device__ __forceinline__ void tma_store_2d(const CUtensorMap* tm, uint32_t src, int c0, int c1) {
  asm volatile("cp.async.bulk.tensor.2d.global.shared::cta.bulk_group [%0, {%2, %3}], [%1];" ::"l"(tm), "r"(src),
               "r"(c0), "r"(c1)
               : "memory");
}
__device__ __forceinline__ void wgmma_fence() { asm volatile("wgmma.fence.sync.aligned;" ::: "memory"); }
__device__ __forceinline__ void wgmma_commit() { asm volatile("wgmma.commit_group.sync.aligned;" ::: "memory"); }
template <int N>
__device__ __forceinline__ void wgmma_wait() {
  asm volatile("wgmma.wait_group.sync.aligned %0;" ::"n"(N) : "memory");
}
__device__ __forceinline__ uint64_t smem_desc(uint32_t addr) {
  return (uint64_t)((addr & 0x3FFFF) >> 4) | (1ull << 16) | (64ull << 32) | (1ull << 62);
}
__device__ __forceinline__ uint32_t bf16x2_fma(uint32_t a, uint32_t b, uint32_t c) {
  uint32_t d;
  asm("fma.rn.bf16x2 %0, %1, %2, %3;" : "=r"(d) : "r"(a), "r"(b), "r"(c));
  return d;
}
__device__ __forceinline__ uint32_t bf16x2_mul(uint32_t a, uint32_t b) {
  uint32_t d;
  asm("mul.rn.bf16x2 %0, %1, %2;" : "=r"(d) : "r"(a), "r"(b));
  return d;
}

template <int ACC>
__device__ __forceinline__ void wgmma_rs_n128(float (&d)[64], uint32_t a0, uint32_t a1, uint32_t a2, uint32_t a3,
                                              uint64_t desc_b) {
  asm volatile(
      "{\n.reg .pred p;\nsetp.ne.b32 p, %69, 0;\n"
      "wgmma.mma_async.sync.aligned.m64n128k16.f32.bf16.bf16 {"
      "%0, %1, %2, %3, %4, %5, %6, %7, %8, %9, %10, %11, %12, %13, %14, %15, "
      "%16, %17, %18, %19, %20, %21, %22, %23, %24, %25, %26, %27, %28, %29, %30, %31, "
      "%32, %33, %34, %35, %36, %37, %38, %39, %40, %41, %42, %43, %44, %45, %46, %47, "
      "%48, %49, %50, %51, %52, %53, %54, %55, %56, %57, %58, %59, %60, %61, %62, %63"
      "}, {%64, %65, %66, %67}, %68, p, 1, 1, 0;\n}\n"
      : "+f"(d[0]), "+f"(d[1]), "+f"(d[2]), "+f"(d[3]), "+f"(d[4]), "+f"(d[5]), "+f"(d[6]), "+f"(d[7]),
        "+f"(d[8]), "+f"(d[9]), "+f"(d[10]), "+f"(d[11]), "+f"(d[12]), "+f"(d[13]), "+f"(d[14]), "+f"(d[15]),
        "+f"(d[16]), "+f"(d[17]), "+f"(d[18]), "+f"(d[19]), "+f"(d[20]), "+f"(d[21]), "+f"(d[22]), "+f"(d[23]),
        "+f"(d[24]), "+f"(d[25]), "+f"(d[26]), "+f"(d[27]), "+f"(d[28]), "+f"(d[29]), "+f"(d[30]), "+f"(d[31]),
        "+f"(d[32]), "+f"(d[33]), "+f"(d[34]), "+f"(d[35]), "+f"(d[36]), "+f"(d[37]), "+f"(d[38]), "+f"(d[39]),
        "+f"(d[40]), "+f"(d[41]), "+f"(d[42]), "+f"(d[43]), "+f"(d[44]), "+f"(d[45]), "+f"(d[46]), "+f"(d[47]),
        "+f"(d[48]), "+f"(d[49]), "+f"(d[50]), "+f"(d[51]), "+f"(d[52]), "+f"(d[53]), "+f"(d[54]), "+f"(d[55]),
        "+f"(d[56]), "+f"(d[57]), "+f"(d[58]), "+f"(d[59]), "+f"(d[60]), "+f"(d[61]), "+f"(d[62]), "+f"(d[63])
      : "r"(a0), "r"(a1), "r"(a2), "r"(a3), "l"(desc_b), "n"(ACC));
}

template <int ACC>
__device__ __forceinline__ void wgmma_rs_n104(float (&d)[64], uint32_t a0, uint32_t a1, uint32_t a2, uint32_t a3,
                                              uint64_t desc_b) {
  asm volatile(
      "{\n.reg .pred p;\nsetp.ne.b32 p, %57, 0;\n"
      "wgmma.mma_async.sync.aligned.m64n104k16.f32.bf16.bf16 {"
      "%0, %1, %2, %3, %4, %5, %6, %7, %8, %9, %10, %11, %12, %13, %14, %15, "
      "%16, %17, %18, %19, %20, %21, %22, %23, %24, %25, %26, %27, %28, %29, %30, %31, "
      "%32, %33, %34, %35, %36, %37, %38, %39, %40, %41, %42, %43, %44, %45, %46, %47, "
      "%48, %49, %50, %51"
      "}, {%52, %53, %54, %55}, %56, p, 1, 1, 0;\n}\n"
      : "+f"(d[0]), "+f"(d[1]), "+f"(d[2]), "+f"(d[3]), "+f"(d[4]), "+f"(d[5]), "+f"(d[6]), "+f"(d[7]),
        "+f"(d[8]), "+f"(d[9]), "+f"(d[10]), "+f"(d[11]), "+f"(d[12]), "+f"(d[13]), "+f"(d[14]), "+f"(d[15]),
        "+f"(d[16]), "+f"(d[17]), "+f"(d[18]), "+f"(d[19]), "+f"(d[20]), "+f"(d[21]), "+f"(d[22]), "+f"(d[23]),
        "+f"(d[24]), "+f"(d[25]), "+f"(d[26]), "+f"(d[27]), "+f"(d[28]), "+f"(d[29]), "+f"(d[30]), "+f"(d[31]),
        "+f"(d[32]), "+f"(d[33]), "+f"(d[34]), "+f"(d[35]), "+f"(d[36]), "+f"(d[37]), "+f"(d[38]), "+f"(d[39]),
        "+f"(d[40]), "+f"(d[41]), "+f"(d[42]), "+f"(d[43]), "+f"(d[44]), "+f"(d[45]), "+f"(d[46]), "+f"(d[47]),
        "+f"(d[48]), "+f"(d[49]), "+f"(d[50]), "+f"(d[51])
      : "r"(a0), "r"(a1), "r"(a2), "r"(a3), "l"(desc_b), "n"(ACC));
}

template <int ACC>
__device__ __forceinline__ void wgmma_ss_n104(float (&d)[64], uint64_t desc_a, uint64_t desc_b) {
  asm volatile(
      "{\n.reg .pred p;\nsetp.ne.b32 p, %54, 0;\n"
      "wgmma.mma_async.sync.aligned.m64n104k16.f32.bf16.bf16 {"
      "%0, %1, %2, %3, %4, %5, %6, %7, %8, %9, %10, %11, %12, %13, %14, %15, "
      "%16, %17, %18, %19, %20, %21, %22, %23, %24, %25, %26, %27, %28, %29, %30, %31, "
      "%32, %33, %34, %35, %36, %37, %38, %39, %40, %41, %42, %43, %44, %45, %46, %47, "
      "%48, %49, %50, %51"
      "}, %52, %53, p, 1, 1, 1, 0;\n}\n"
      : "+f"(d[0]), "+f"(d[1]), "+f"(d[2]), "+f"(d[3]), "+f"(d[4]), "+f"(d[5]), "+f"(d[6]), "+f"(d[7]),
        "+f"(d[8]), "+f"(d[9]), "+f"(d[10]), "+f"(d[11]), "+f"(d[12]), "+f"(d[13]), "+f"(d[14]), "+f"(d[15]),
        "+f"(d[16]), "+f"(d[17]), "+f"(d[18]), "+f"(d[19]), "+f"(d[20]), "+f"(d[21]), "+f"(d[22]), "+f"(d[23]),
        "+f"(d[24]), "+f"(d[25]), "+f"(d[26]), "+f"(d[27]), "+f"(d[28]), "+f"(d[29]), "+f"(d[30]), "+f"(d[31]),
        "+f"(d[32]), "+f"(d[33]), "+f"(d[34]), "+f"(d[35]), "+f"(d[36]), "+f"(d[37]), "+f"(d[38]), "+f"(d[39]),
        "+f"(d[40]), "+f"(d[41]), "+f"(d[42]), "+f"(d[43]), "+f"(d[44]), "+f"(d[45]), "+f"(d[46]), "+f"(d[47]),
        "+f"(d[48]), "+f"(d[49]), "+f"(d[50]), "+f"(d[51])
      : "l"(desc_a), "l"(desc_b), "n"(ACC));
}

__host__ __device__ constexpr bool use_imad(int b) { return (IMASK >> b) & 1; }
struct Dq {
  uint32_t addr[5], sh[5];
  uint32_t c[2], s[2];
  int tj;
};

template <int PITCH>
__device__ __forceinline__ void dq_setup(Dq& q, uint32_t base, int phase) {
  const int lane = threadIdx.x & 31;
  q.tj = (lane & 3) - phase;
#pragma unroll
  for (int b = 0; b < 5; ++b) {
    const int e = 4 * b + q.tj + 5;
    const int o = (e * 52) >> 8;
    q.addr[b] = base + (o - 1) * PITCH;
    q.sh[b] = 6 * (e - 5 * o);
    if (use_imad(b)) asm("shr.u32 %0, 0x1000000, %1;" : "=r"(q.sh[b]) : "r"(q.sh[b]));
  }
}
__device__ __forceinline__ void dq_consts(Dq& q, int h, uint16_t z, uint16_t s) {
  q.c[h] = bf16x2_mul((uint32_t)z * 0x10001u, 0xBE00BC80u);
  q.s[h] = bf16x2_mul((uint32_t)s * 0x10001u, 0x41004280u);
}
template <int R0, int NR, int PITCH = kWPitch, int DST = R0>
__device__ __forceinline__ void dq_load(uint32_t (&a)[144], const Dq& q) {
#pragma unroll
  for (int i = R0; i < R0 + NR; ++i)
    asm volatile("ld.shared.u32 %0, [%1];"
                 : "=r"(a[i - R0 + DST])
                 : "r"(q.addr[(i >> 1) % 5] + ((i >> 1) / 5) * 4 * PITCH + (i & 1) * 32));
}
template <int R0, int NR, int DST = R0>
__device__ __forceinline__ void dq_math(uint32_t (&a)[144], const Dq& q) {
#pragma unroll
  for (int i = R0; i < R0 + NR; ++i) {
    const int u = i >> 1, h = i & 1;
    uint32_t w = a[i - R0 + DST];
    if (use_imad(u % 5)) w = __byte_perm(w * q.sh[u % 5], 0, 0x3333);
    else w = __byte_perm(w >> q.sh[u % 5], 0, 0x0000);
    w &= 0x00380007u;
    w = bf16x2_mul(bf16x2_fma(w, 0x7F007F00u, q.c[h]), q.s[h]);
    if (u == 0) w = q.tj < 0 ? 0u : w;
    if (u == 71) w = q.tj > 0 ? 0u : w;
    a[i - R0 + DST] = w;
  }
}
template <int R0, int NR, int PITCH = kWPitch, int DST = R0>
__device__ __forceinline__ void dq_regs(uint32_t (&a)[144], const Dq& q) {
  dq_load<R0, NR, PITCH, DST>(a, q);
  dq_math<R0, NR, DST>(a, q);
}

template <int C>
__device__ __forceinline__ void mma_chunk(float (&d)[64], const uint32_t (&a)[144], uint64_t desc) {
  wgmma_fence();
#pragma unroll
  for (int s = 4 * C; s < 4 * C + 4; ++s) {
    if (s == 0) wgmma_rs_n128<0>(d, a[0], a[1], a[2], a[3], desc);
    else wgmma_rs_n128<1>(d, a[4 * s], a[4 * s + 1], a[4 * s + 2], a[4 * s + 3], desc + 2 * (s & 3));
  }
  wgmma_commit();
}
template <int C>
__device__ __forceinline__ void mma_chunk_extra(float (&d)[64], const uint32_t (&a)[144], uint64_t desc_a,
                                                uint64_t desc) {
  wgmma_fence();
#pragma unroll
  for (int kk = 0; kk < 4; ++kk) {
    if (C < kSS) {
      if (C == 0 && kk == 0) wgmma_ss_n104<0>(d, desc_a, desc);
      else wgmma_ss_n104<1>(d, desc_a + 128 * kk, desc + 2 * kk);
    } else {
      const int r = (16 * (C - kSS) + 4 * kk) % 144;
      wgmma_rs_n104<1>(d, a[r], a[r + 1], a[r + 2], a[r + 3], desc + 2 * kk);
    }
  }
  wgmma_commit();
}

#define BOUNDARY(I) \
  asm volatile("{\n.reg .pred p;\nsetp.ne.s32 p, %0, %1;\n@p bra.uni OK;\ntrap;\nOK:\n}" ::"r"(cx.wg), "n"((I) + 100) : "memory")
#define SPLIT2 0
#define STGATE 1
#define BND1 1
#define BND2 0

struct Ctx {
  uint32_t sb;
  uint32_t empty_dst;
  uint64_t desc;
  int wg;
  bool extra;
  int phase_e;
};

template <int G>
__device__ __forceinline__ void release(const Ctx& cx) {
  if (G + kStages >= 5 * kChunks) return;
  if ((G + kStages < 4 * kChunks || cx.extra) && (threadIdx.x & 31) < 2)
    asm volatile("mbarrier.arrive.shared::cluster.b64 _, [%0];" ::"r"(cx.empty_dst + ((G + kStages) % kStages) * 8) : "memory");
}

__device__ __forceinline__ void wg_sync(int wg) {
  if (wg == 0) asm volatile("bar.sync 3, 128;" ::: "memory");
  else asm volatile("bar.sync 4, 128;" ::: "memory");
}

template <int MODE, int T, int C>
__device__ __forceinline__ void tile_step(float (&d)[64], uint32_t (&a)[144], Dq& q, const Ctx& cx) {
  constexpr int G = T * kChunks + C, S = G % kStages;
  constexpr int lag = T == 0 ? LAG0 : T == 3 ? LAG3 : LAG1;
  const uint32_t sb = cx.sb;
  mbar_wait(sb + kBarFull + S * 8, (G / kStages) & 1);
  if (MODE != 3 && C == 0 && cx.wg == 1) asm volatile("bar.sync 1, 256;" ::: "memory");
  if (GATE && T == 3 && MODE == 0 && C == GATE && cx.wg == 1 && cx.extra) asm volatile("bar.sync 7, 256;" ::: "memory");
  TR(cx.wg, T * 11 + C);
  if (MODE == 3) mma_chunk_extra<C>(d, a, cx.desc + (kOffAx + C * 8192) / 16, cx.desc + S * (kStageBytes / 16));
  else mma_chunk<C>(d, a, cx.desc + S * (kStageBytes / 16));
  if (MODE != 3 && lag == C && cx.wg == 0) asm volatile("bar.arrive 1, 256;" ::: "memory");
  if (GATE && MODE == 2 && C == 8) asm volatile("bar.arrive 7, 256;" ::: "memory");
  if (MODE == 1 && C < 8 && kPer > 0) {
    if (BND1) BOUNDARY(C);
    if (!SPLIT1) dq_load<(kPre + C * kPer) % 144, kPer>(a, q);
    dq_math<(kPre + C * kPer) % 144, kPer>(a, q);
  }
  if (MODE == 2 && C == 0) {
    const int cole = ((threadIdx.x >> 5) & 3) * 16 + ((threadIdx.x & 31) >> 2);
    dq_setup<kWePitch>(q, sb + kOffWe - kWeRow0 * kWePitch + cole * 4, cx.phase_e);
    mbar_wait(sb + kBarW1, 0);
#pragma unroll
    for (int h = 0; h < 2; ++h) {
      uint16_t z, s;
      asm volatile("ld.shared.u16 %0, [%1];" : "=h"(z) : "r"(sb + kOffZS + (cole + 8 * h) * 2));
      asm volatile("ld.shared.u16 %0, [%1];" : "=h"(s) : "r"(sb + kOffZS + 128 + (cole + 8 * h) * 2));
      dq_consts(q, h, z, s);
    }
  }
  if (MODE == 2 && C >= 2) {
    if (BND2) BOUNDARY(30 + C);
    if (!SPLIT2) dq_load<16 * kSS + trail_end(C - 1), trail_end(C) - trail_end(C - 1), kWePitch, trail_end(C - 1)>(a, q);
    dq_math<16 * kSS + trail_end(C - 1), trail_end(C) - trail_end(C - 1), trail_end(C - 1)>(a, q);
  }
  if (C > 0 && MODE != 3) wgmma_wait<1>();
  if (MODE == 1 && SPLIT1 && C < 7 && kPer > 0) dq_load<(kPre + (C + 1) * kPer) % 144, kPer>(a, q);
  if (MODE == 2 && SPLIT2 && C >= 1 && C < 8)
    dq_load<16 * kSS + trail_end(C), trail_end(C + 1) - trail_end(C), kWePitch, trail_end(C)>(a, q);
  if (C > 0 && MODE != 3) release<G - 1>(cx);
}

template <int MODE, int T>
__device__ __forceinline__ void tile(float (&d)[64], uint32_t (&a)[144], Dq& q, Ctx& cx, uint32_t zero) {
  constexpr int N = MODE == 3 ? kNX : 128;
  cx.sb += zero;
  cx.desc += zero;
  const uint32_t sb = cx.sb;
  tile_step<MODE, T, 0>(d, a, q, cx);
  tile_step<MODE, T, 1>(d, a, q, cx);
  tile_step<MODE, T, 2>(d, a, q, cx);
  tile_step<MODE, T, 3>(d, a, q, cx);
  tile_step<MODE, T, 4>(d, a, q, cx);
  tile_step<MODE, T, 5>(d, a, q, cx);
  tile_step<MODE, T, 6>(d, a, q, cx);
  tile_step<MODE, T, 7>(d, a, q, cx);
  tile_step<MODE, T, 8>(d, a, q, cx);
  const int lane = threadIdx.x & 31, warp = (threadIdx.x >> 5) & 3;
  if (MODE == 1 && lane == 0) mbar_arrive(sb + kBarDq);
  if (T > 0) mbar_wait(sb + kBarOutFree + cx.wg * 8, (T - 1) & 1);
  wgmma_wait<0>();
#pragma unroll
  for (int i = 0; i < N / 2; ++i) asm volatile("" : "+f"(d[i])::"memory");
  if (MODE != 3) release<T * kChunks + 8>(cx);
  TR(cx.wg, T * 11 + 9);
  const uint32_t st = sb + kOffOut + cx.wg * 16384 + ((lane & 7) + ((lane >> 4) << 3)) * 128 +
                      (((warp * 2 + ((lane >> 3) & 1)) ^ (lane & 7)) << 4);
#pragma unroll
  for (int i = 0; i < N / 8; i += 2) {
    uint32_t r0, r1, r2, r3;
    asm("cvt.rn.bf16x2.f32 %0, %1, %2;" : "=r"(r0) : "f"(d[4 * i + 1]), "f"(d[4 * i]));
    asm("cvt.rn.bf16x2.f32 %0, %1, %2;" : "=r"(r1) : "f"(d[4 * i + 3]), "f"(d[4 * i + 2]));
    if (i + 1 < N / 8) {
      asm("cvt.rn.bf16x2.f32 %0, %1, %2;" : "=r"(r2) : "f"(d[4 * i + 5]), "f"(d[4 * i + 4]));
      asm("cvt.rn.bf16x2.f32 %0, %1, %2;" : "=r"(r3) : "f"(d[4 * i + 7]), "f"(d[4 * i + 6]));
      asm volatile("stmatrix.sync.aligned.m8n8.x4.trans.shared.b16 [%0], {%1, %2, %3, %4};" ::"r"(st + i * 1024),
                   "r"(r0), "r"(r1), "r"(r2), "r"(r3)
                   : "memory");
    } else {
      asm volatile("stmatrix.sync.aligned.m8n8.x2.trans.shared.b16 [%0], {%1, %2};" ::"r"(st + i * 1024), "r"(r0),
                   "r"(r1)
                   : "memory");
    }
  }
  asm volatile("fence.proxy.async.shared::cta;" ::: "memory");
  __syncwarp();
  if (lane == 0) mbar_arrive(sb + kBarOutFull + cx.wg * 8);
  if (T < 4) TR(cx.wg, T * 11 + 10);
}

__global__ void __cluster_dims__(2, 1, 1) __launch_bounds__(384, 1)
    gptq_gemm_kernel(const uint32_t* __restrict__ qw, const __nv_bfloat16* __restrict__ scales,
                     const __nv_bfloat16* __restrict__ zeros, const uint32_t zero,
                     const __grid_constant__ CUtensorMap tm_x64, const __grid_constant__ CUtensorMap tm_w,
                     const __grid_constant__ CUtensorMap tm_o128, const __grid_constant__ CUtensorMap tm_x52,
                     const __grid_constant__ CUtensorMap tm_o104, const __grid_constant__ CUtensorMap tm_we) {
  extern __shared__ __align__(1024) uint8_t smem[];
  const uint32_t sb = (uint32_t)__cvta_generic_to_shared(smem);
  const int cid = blockIdx.x >> 1, rank = blockIdx.x & 1;
  const int phase = cid & 3, n_own = (cid >> 2) * 256 + rank * 128;
  const int warp_id = __shfl_sync(0xffffffffu, (int)(threadIdx.x >> 5), 0);
  const int wg = warp_id >> 2;
  const int lane = threadIdx.x & 31;
  const int col = warp_id * 16 + (lane >> 2);
  uint16_t z0, z1, s0, s1;

  if ((threadIdx.x >> 5) != 8) asm volatile("barrier.cluster.arrive.relaxed.aligned;" ::: "memory");
  if (warp_id < 8) {
    const int tid = threadIdx.x & 127;
    const uint32_t* src = qw + ((tid >> 4) * kF + n_own + wg * 64 + (tid & 15) * 4);
    const uint32_t dst = sb + kOffW + (tid >> 4) * kWPitch + wg * 256 + (tid & 15) * 16;
#pragma unroll
    for (int i = 0; i < kFirst; ++i) {
      asm volatile("cp.async.cg.shared.global [%0], [%1], 16;" ::"r"(dst + i * 8 * kWPitch), "l"(src + i * 8 * kF)
                   : "memory");
      if (i == 0) {
        asm volatile("cp.async.commit_group;" ::: "memory");
        TR(wg, 59);
        const uint16_t* zp = reinterpret_cast<const uint16_t*>(zeros) + (n_own + col);
        const uint16_t* sp = reinterpret_cast<const uint16_t*>(scales) + (n_own + col);
        asm volatile("ld.global.nc.u16 %0, [%1];" : "=h"(z0) : "l"(zp));
        asm volatile("ld.global.nc.u16 %0, [%1+16];" : "=h"(z1) : "l"(zp));
        asm volatile("ld.global.nc.u16 %0, [%1];" : "=h"(s0) : "l"(sp));
        asm volatile("ld.global.nc.u16 %0, [%1+16];" : "=h"(s1) : "l"(sp));
      }
    }
    asm volatile("cp.async.commit_group;" ::: "memory");
  }

  const bool has_extra = cid < kExtraClusters;
  const int ue = kClusters + cid / 10;
  const int phase_e = ue & 3, n_e = (ue >> 2) * 256 + ((cid / 5) & 1) * 128 + rank * 64, row_e = (cid % 5) * kNX;

  if (wg == 2) {
    asm volatile("setmaxnreg.dec.sync.aligned.u32 24;");
    if (warp_id == 8) {
      const bool leader = elect_one();
      if (leader) {
        TRALL(2, 56);
#pragma unroll
        for (int i = 0; i < kStages; ++i) mbar_init(sb + kBarFull + 8 * i, 1);
        asm volatile("fence.mbarrier_init.release.cluster;" ::: "memory");
        TRALL(2, 57);
      }
      __syncwarp();
      asm volatile("barrier.cluster.arrive.relaxed.aligned;" ::: "memory");
      asm volatile("barrier.cluster.wait.aligned;" ::: "memory");
      uint32_t t0;
      if (leader) {
        TRALL(2, 59);
        mbar_expect_tx(sb + kBarFull, kStageBytes);
        tma_load_2d_mc(sb + rank * 8192, &tm_x64, sb + kBarFull, phase * 568, rank * 64);
        TRALL(2, 0);
#pragma unroll
        for (int i = 0; i < kStages; ++i) mbar_init(sb + kBarEmpty + 8 * i, 16);
        mbar_init(sb + kBarW1, 1);
        mbar_init(sb + kBarDq, 8);
        mbar_init(sb + kBarAx, 2);
        mbar_init(sb + kBarLd, 1);
        mbar_init(sb + kBarOutFull, 4);
        mbar_init(sb + kBarOutFull + 8, 4);
        mbar_init(sb + kBarOutFree, 1);
        mbar_init(sb + kBarOutFree + 8, 1);
        asm volatile("fence.mbarrier_init.release.cluster;" ::: "memory");
      }
      asm volatile("mov.u32 %0, %clock;" : "=r"(t0));
      __syncwarp();
      asm volatile("bar.arrive 2, 288;" ::: "memory");
      asm volatile("bar.arrive 5, 128;" ::: "memory");
      if (leader) {
#pragma unroll
        for (int g = 1; g < kStages; ++g) {
          const uint32_t full = sb + kBarFull + g * 8;
          uint32_t t;
          do { asm volatile("mov.u32 %0, %clock;" : "=r"(t)); } while (t - t0 < g * PACE);
          TRALL(2, g);
          uint32_t bytes = kStageBytes;
#pragma unroll
          for (int p = kFirst; p < 8; ++p)
            if (need_step(p) == g) bytes += p < 7 ? 8 * kWPitch : 512;
          mbar_expect_tx(full, bytes);
          tma_load_2d_mc(sb + g * kStageBytes + rank * 8192, &tm_x64, full, phase * 568 + (g % kChunks) * 64,
                         rank * 64 + (g / kChunks) * 128);
#pragma unroll
          for (int p = kFirst; p < 8; ++p)
            if (need_step(p) == g) {
              if (p < 7) tma_load_2d(sb + kOffW + p * 8 * kWPitch, &tm_w, full, n_own, p * 8);
              else bulk_load(sb + kOffW + 56 * kWPitch, qw + 56 * kF + n_own, 512, full);
            }
        }
        const int total = has_extra ? 5 * kChunks : 4 * kChunks;
        int c = kStages % kChunks, row = rank * 64 + (kStages / kChunks) * 128;
        uint32_t stage = 0, parity = 0;
#pragma unroll 1
        for (int g = kStages; g < total; ++g) {
          const uint32_t full = sb + kBarFull + stage * 8, dst = sb + stage * kStageBytes;
          mbar_wait_lazy(sb + kBarEmpty + stage * 8, parity);
          TRALL(2, g);
          if (g < 4 * kChunks) {
            mbar_expect_tx(full, kStageBytes);
            tma_load_2d_mc(dst + rank * 8192, &tm_x64, full, phase * 568 + c * 64, row);
          } else {
            mbar_expect_tx(full, kNX * 128);
            tma_load_2d_mc(dst + rank * (kNX * 64), &tm_x52, full, phase_e * 568 + c * 64, row_e + rank * (kNX / 2));
          }
          if (++c == kChunks) { c = 0; row += 128; }
          if (++stage == kStages) { stage = 0; parity ^= 1; }
        }
        if (STGATE) mbar_arrive(sb + kBarLd);
      }
    } else if (warp_id == 9) {
      asm volatile("prefetch.tensormap [%0];" ::"l"(&tm_x64) : "memory");
      asm volatile("prefetch.tensormap [%0];" ::"l"(&tm_w) : "memory");
      asm volatile("bar.sync 5, 128;" ::: "memory");
      if (elect_one()) {
        const int nst = has_extra ? 9 : 8;
#pragma unroll 1
        for (int i = 0; i < nst; ++i) {
          const int w = i & 1, t = i >> 1;
          if (i >= 7) mbar_wait(sb + kBarOutFull + w * 8, t & 1);
          else mbar_wait_lazy(sb + kBarOutFull + w * 8, t & 1);
          if (STGATE && i == 6) mbar_wait_lazy(sb + kBarLd, 0);
          TRALL(3, 2 * i);
          if (i < 8) tma_store_2d(&tm_o128, sb + kOffOut + w * 16384, phase * kF + n_own + w * 64, t * 128);
          else tma_store_2d(&tm_o104, sb + kOffOut, phase_e * kF + n_e, row_e);
          asm volatile("cp.async.bulk.commit_group;" ::: "memory");
          if (i < 7) {
            asm volatile("cp.async.bulk.wait_group.read 0;" ::: "memory");
            mbar_arrive(sb + kBarOutFree + w * 8);
          }
          TRALL(3, 2 * i + 1);
        }
        asm volatile("cp.async.bulk.wait_group.read 0;" ::: "memory");
      }
    } else {
      asm volatile("bar.sync 5, 128;" ::: "memory");
      if (has_extra) {
        const int h = threadIdx.x - 320, c4 = h & 15;
        const int colx = n_e + c4 * 4;
        mbar_wait_lazy(sb + kBarDq, 0);
        TR(3, 32 + (warp_id & 1));
        if (warp_id == 11 && elect_one()) {
          mbar_expect_tx(sb + kBarW1, kWeRows * kWePitch + 256);
          tma_load_2d(sb + kOffWe, &tm_we, sb + kBarW1, n_e, kWeRow0);
          bulk_load(sb + kOffZS, zeros + n_e, 128, sb + kBarW1);
          bulk_load(sb + kOffZS + 128, scales + n_e, 128, sb + kBarW1);
        }
        __syncwarp();
        uint32_t src = sb + kOffHead + (h >> 4) * 256 + c4 * 16;
#pragma unroll
        for (int i = 0; i < (kHeadRows + 3) / 4; ++i)
          if (4 * i + 3 < kHeadRows || 4 * i + (h >> 4) < kHeadRows)
            asm volatile("cp.async.cg.shared.global [%0], [%1], 16;" ::"r"(src + i * 1024),
                         "l"(qw + ((h >> 4) + 4 * i) * kF + colx)
                         : "memory");
        uint32_t c[2], s[2];
        {
          const uint2 z2 = __ldg(reinterpret_cast<const uint2*>(zeros + colx));
          const uint2 s2 = __ldg(reinterpret_cast<const uint2*>(scales + colx));
          c[0] = bf16x2_mul(z2.x, 0xBC80BC80u); c[1] = bf16x2_mul(z2.y, 0xBC80BC80u);
          s[0] = bf16x2_mul(s2.x, 0x42804280u); s[1] = bf16x2_mul(s2.y, 0x42804280u);
        }
        if (h < 16 * phase_e)
          asm volatile("st.shared.v4.u32 [%0], {%1, %1, %1, %1};" ::"r"(sb + kOffAx + h * 16), "r"(0u) : "memory");
        uint32_t row = sb + kOffAx + (10 * (h >> 4) + 2 * phase_e) * 128 + c4 * 8;
        const uint32_t src_end = sb + kOffHead + kHeadRows * 256;
        asm volatile("cp.async.wait_all;" ::: "memory");
#pragma unroll 1
        for (; src < src_end; src += 1024, row += 40 * 128) {
          uint4 w;
          asm volatile("ld.shared.v4.u32 {%0, %1, %2, %3}, [%4];"
                       : "=r"(w.x), "=r"(w.y), "=r"(w.z), "=r"(w.w)
                       : "r"(src)
                       : "memory");
          uint32_t win[2], ad;
#pragma unroll
          for (int i = 0; i < 10; ++i) {
            constexpr uint32_t sel[4] = {0x5410, 0x6521, 0x7632, 0x7733};
            constexpr int pos[10] = {0, 3, 2, 1, 4, 3, 2, 5, 0, 3};
            if (i == 0 || i == 3 || i == 6 || i == 8) {
              const uint32_t se = sel[i == 0 ? 0 : i == 3 ? 1 : i == 6 ? 2 : 3];
              win[0] = __byte_perm(w.x, w.y, se);
              win[1] = __byte_perm(w.z, w.w, se);
            }
            uint32_t v[2];
#pragma unroll
            for (int j = 0; j < 2; ++j) {
              const uint32_t f = ((i == 2 || i == 5) ? win[j] >> 4 : win[j]) & (0x00070007u << pos[i]);
              v[j] = bf16x2_mul(bf16x2_fma(f, 0x7F007F00u - pos[i] * 0x00800080u, c[j]), s[j]);
            }
            if ((i & 1) == 0) {
              asm volatile("{\n.reg .u32 t;\nadd.u32 %0, %1, %2;\nshr.u32 t, %0, 3;\nlop3.b32 %0, %0, t, 0x70, 0x78;\n}"
                           : "=r"(ad)
                           : "r"(row), "r"(i * 128));
              asm volatile("st.shared.v2.u32 [%0], {%1, %2};" ::"r"(ad), "r"(v[0]), "r"(v[1]) : "memory");
            } else {
              asm volatile("st.shared.v2.u32 [%0+128], {%1, %2};" ::"r"(ad ^ 16), "r"(v[0]), "r"(v[1]) : "memory");
            }
          }
        }
        asm volatile("fence.proxy.async.shared::cta;" ::: "memory");
        __syncwarp();
        if (lane == 0) mbar_arrive(sb + kBarAx);
        TR(3, 34 + (warp_id & 1));
      }
    }
  } else {
    TR(wg, 54);
    asm volatile("setmaxnreg.inc.sync.aligned.u32 240;");
    Ctx cx;
    cx.sb = sb;
    cx.wg = wg;
    cx.extra = has_extra;
    cx.phase_e = phase_e;
    cx.desc = smem_desc(sb);
    asm("mapa.shared::cluster.u32 %0, %1, %2;" : "=r"(cx.empty_dst) : "r"(sb + kBarEmpty), "r"(lane & 1));
    float d[64];
    uint32_t a[144];
    Dq q;
    dq_setup<kWPitch>(q, sb + kOffW + col * 4, phase);
    dq_consts(q, 0, z0, s0);
    dq_consts(q, 1, z1, s1);
    asm volatile("cp.async.wait_group 1;" ::: "memory");
    wg_sync(wg);
    TR(wg, 58);
    dq_regs<0, 16>(a, q);
    asm volatile("cp.async.wait_group 0;" ::: "memory");
    wg_sync(wg);
    TR(wg, 57);
    if (kPre > 16) dq_regs<16, kPre - 16>(a, q);
    if (SPLIT1 && kPer > 0) dq_load<kPre % 144, kPer>(a, q);
    TR(wg, 56);
    asm volatile("bar.sync 2, 288;" ::: "memory");
    TR(wg, 55);
    tile<1, 0>(d, a, q, cx, zero);
    tile<0, 1>(d, a, q, cx, zero);
    tile<0, 2>(d, a, q, cx, zero);
    if (wg == 0 && has_extra) {
      tile<2, 3>(d, a, q, cx, zero);
      mbar_wait(sb + kBarAx, 0);
      tile<3, 4>(d, a, q, cx, zero);
    } else {
      tile<0, 3>(d, a, q, cx, zero);
    }
  }
}

typedef CUresult (*EncodeFn)(CUtensorMap*, CUtensorMapDataType, cuuint32_t, void*, const cuuint64_t*,
                             const cuuint64_t*, const cuuint32_t*, const cuuint32_t*, CUtensorMapInterleave,
                             CUtensorMapSwizzle, CUtensorMapL2promotion, CUtensorMapFloatOOBfill);

void make_map(EncodeFn enc, CUtensorMap* tm, CUtensorMapDataType dt, const void* base, uint64_t d0, uint64_t d1,
              uint64_t stride, uint32_t b0, uint32_t b1, CUtensorMapSwizzle sw, CUtensorMapL2promotion promo) {
  cuuint64_t dims[2] = {d0, d1};
  cuuint64_t strides[1] = {stride};
  cuuint32_t box[2] = {b0, b1};
  cuuint32_t es[2] = {1, 1};
  enc(tm, dt, 2, const_cast<void*>(base), dims, strides, box, es, CU_TENSOR_MAP_INTERLEAVE_NONE, sw, promo,
      CU_TENSOR_MAP_FLOAT_OOB_FILL_NONE);
}

}

extern "C" void kernel_launch(void* const* d_in, const int* in_sizes, int n_in, void* d_out, int out_size) {
  (void)in_sizes; (void)n_in; (void)out_size;
  static EncodeFn enc = nullptr;
  if (!enc) {
    void* fn = nullptr;
    cudaDriverEntryPointQueryResult qr;
    cudaGetDriverEntryPoint("cuTensorMapEncodeTiled", &fn, cudaEnableDefault, &qr);
    enc = (EncodeFn)fn;
    cudaFuncSetAttribute(gptq_gemm_kernel, cudaFuncAttributeMaxDynamicSharedMemorySize, kSmemBytes);
  }
  CUtensorMap x64, x52, w, we, o128, o104;
  make_map(enc, &x64, CU_TENSOR_MAP_DATA_TYPE_BFLOAT16, d_in[0], 2280, kSup, 4560, 64, 64, CU_TENSOR_MAP_SWIZZLE_128B,
           CU_TENSOR_MAP_L2_PROMOTION_L2_128B);
  make_map(enc, &x52, CU_TENSOR_MAP_DATA_TYPE_BFLOAT16, d_in[0], 2280, kSup, 4560, 64, kNX / 2,
           CU_TENSOR_MAP_SWIZZLE_128B, CU_TENSOR_MAP_L2_PROMOTION_L2_128B);
  make_map(enc, &w, CU_TENSOR_MAP_DATA_TYPE_INT32, d_in[1], kF, 57, kF * 4, 136, 8, CU_TENSOR_MAP_SWIZZLE_NONE,
           CU_TENSOR_MAP_L2_PROMOTION_L2_128B);
  make_map(enc, &we, CU_TENSOR_MAP_DATA_TYPE_INT32, d_in[1], kF, 57, kF * 4, 72, kWeRows, CU_TENSOR_MAP_SWIZZLE_NONE,
           CU_TENSOR_MAP_L2_PROMOTION_L2_128B);
  make_map(enc, &o128, CU_TENSOR_MAP_DATA_TYPE_BFLOAT16, d_out, 4 * kF, kSup, 8 * kF, 64, 128,
           CU_TENSOR_MAP_SWIZZLE_128B, CU_TENSOR_MAP_L2_PROMOTION_NONE);
  make_map(enc, &o104, CU_TENSOR_MAP_DATA_TYPE_BFLOAT16, d_out, 4 * kF, kSup, 8 * kF, 64, kNX,
           CU_TENSOR_MAP_SWIZZLE_128B, CU_TENSOR_MAP_L2_PROMOTION_NONE);
  gptq_gemm_kernel<<<2 * kClusters, 384, kSmemBytes>>>((const uint32_t*)d_in[1], (const __nv_bfloat16*)d_in[2],
                                                       (const __nv_bfloat16*)d_in[3], 0u, x64, w, o128, x52, o104, we);
}
```

```cpp
#include <cuda.h>
#include <cuda_bf16.h>
#include <cuda_runtime.h>
#include <stdint.h>

namespace {

constexpr int kF = 4608;
constexpr int kSup = 512;
constexpr int kChunks = 9;
constexpr int kNX = 104;
constexpr int kClusters = 66;
constexpr int kExtraClusters = 60;

#define LAZY 4000
#define PRE 48
#define LAG0 2
#define LAG1 4
#define LAG3 3
#define GATE 5
#define PACE 400
#define IMASK 10
#define KSS 2
#define STAGES 10
constexpr int kStages = STAGES;
constexpr int kStageBytes = 16384;
constexpr int kWPitch = 544;
constexpr int kWePitch = 288;
constexpr int kSS = KSS;
constexpr int kHeadRows = (64 * kSS + 9) / 10;
constexpr int kWeRow0 = (32 * kSS - 3) / 5;
constexpr int kWeRows = 57 - kWeRow0;
constexpr int kOffOut = kStages * kStageBytes;
constexpr int kOffW = kOffOut + 2 * 16384;
constexpr int kOffAx = kOffW;
constexpr int kOffWe = kOffAx + (10 * kHeadRows + 6) * 128;
constexpr int kOffHead = kOffWe + (kWeRows + 1) * kWePitch;
constexpr int kOffZS = kOffHead + kHeadRows * 256;
constexpr int kOffBar = kOffZS + 256 > kOffW + 58 * kWPitch ? kOffZS + 256 : kOffW + 58 * kWPitch;
constexpr int kBarFull = kOffBar;
constexpr int kBarEmpty = kBarFull + 8 * kStages;
constexpr int kBarW1 = kBarEmpty + 8 * kStages;
constexpr int kBarDq = kBarW1 + 8;
constexpr int kBarAx = kBarDq + 8;
constexpr int kBarLd = kBarAx + 8;
constexpr int kBarFin = kBarLd + 8;
constexpr int kBarOutFull = kBarFin + 8;
constexpr int kBarOutFree = kBarOutFull + 16;
constexpr int kOffTrace = kBarOutFree + 16;

constexpr int kPre = PRE, kPer = (144 - kPre) / 8;
__host__ __device__ constexpr int last_word(int regs) { return (2 * regs - 1) / 5 > 56 ? 56 : (2 * regs - 1) / 5; }
#define SPLIT1 1
constexpr int kFirst = last_word(kPre + (1 + SPLIT1) * kPer) / 8 + 1;
#define LATEW 0
#define XPROMO 2
#define WPROMO 2
#define PACE0 250
#define SPLITST 48
#define EPS 2
#define EBND 1
#define PROL 0
#define NEAR 0
#define PIN 0
#define X0DLY 0
#define NFAST 1
#define W1DLY 0
#define G0 2
#define PFX 0
__host__ __device__ constexpr int need_step(int p) {
  int c = 0;
  while (c < 8 && last_word(kPre + (c + 1 + SPLIT1) * kPer) < 8 * p) ++c;
  return c;
}
__host__ __device__ constexpr int trail_end(int c) {
  return c < 2 ? 0 : ((16 * (kChunks - kSS) * (c - 1) + 13) / 14) * 2 > 16 * (kChunks - kSS)
                         ? 16 * (kChunks - kSS)
                         : ((16 * (kChunks - kSS) * (c - 1) + 13) / 14) * 2;
}

constexpr int kSmemBytes = kOffTrace;
#define TR(role, idx)
#define TRALL(role, idx)
static_assert(kSmemBytes <= 232448, "smem");
static_assert(kFirst <= 7 && kStages >= kChunks, "config");

__device__ __forceinline__ void mbar_init(uint32_t bar, uint32_t cnt) {
  asm volatile("mbarrier.init.shared::cta.b64 [%0], %1;" ::"r"(bar), "r"(cnt) : "memory");
}
__device__ __forceinline__ void mbar_expect_tx(uint32_t bar, uint32_t bytes) {
  asm volatile("mbarrier.arrive.expect_tx.shared::cta.b64 _, [%0], %1;" ::"r"(bar), "r"(bytes) : "memory");
}
__device__ __forceinline__ void mbar_arrive(uint32_t bar) {
  asm volatile("mbarrier.arrive.shared::cta.b64 _, [%0];" ::"r"(bar) : "memory");
}
__device__ __forceinline__ void mbar_wait(uint32_t bar, uint32_t parity) {
  asm volatile(
      "{\n.reg .pred p;\n.reg .u32 it;\n"
      "mbarrier.try_wait.parity.shared::cta.b64 p, [%0], %1;\n"
      "@p bra DONE;\n"
      "mov.u32 it, 0;\n"
      "SPIN:\n"
      "mbarrier.try_wait.parity.shared::cta.b64 p, [%0], %1;\n"
      "@p bra DONE;\n"
      "add.u32 it, it, 1;\n"
      "setp.lt.u32 p, it, 0x100000;\n"
      "@p bra SPIN;\n"
      "trap;\n"
      "DONE:\n}" ::"r"(bar),
      "r"(parity)
      : "memory");
}
__device__ __forceinline__ void mbar_wait_lazy(uint32_t bar, uint32_t parity) {
  asm volatile(
      "{\n.reg .pred p;\n.reg .u32 it;\n"
      "mov.u32 it, 0;\n"
      "SPIN:\n"
      "mbarrier.try_wait.parity.shared::cta.b64 p, [%0], %1, %2;\n"
      "@p bra DONE;\n"
      "add.u32 it, it, 1;\n"
      "setp.lt.u32 p, it, 0x40000;\n"
      "@p bra SPIN;\n"
      "trap;\n"
      "DONE:\n}" ::"r"(bar),
      "r"(parity), "r"(LAZY)
      : "memory");
}
__device__ __forceinline__ bool elect_one() {
  uint32_t p;
  asm volatile("{\n.reg .pred q;\nelect.sync _|q, 0xffffffff;\nselp.u32 %0, 1, 0, q;\n}" : "=r"(p));
  return p;
}
__device__ __forceinline__ void tma_load_2d(uint32_t dst, const CUtensorMap* tm, uint32_t bar, int c0, int c1) {
  asm volatile(
      "cp.async.bulk.tensor.2d.shared::cluster.global.mbarrier::complete_tx::bytes [%0], [%1, {%3, %4}], [%2];" ::"r"(dst),
      "l"(tm), "r"(bar), "r"(c0), "r"(c1)
      : "memory");
}
__device__ __forceinline__ void tma_load_2d_mc(uint32_t dst, const CUtensorMap* tm, uint32_t bar, int c0, int c1) {
  asm volatile(
      "cp.async.bulk.tensor.2d.shared::cluster.global.mbarrier::complete_tx::bytes.multicast::cluster [%0], [%1, {%3, "
      "%4}], [%2], %5;" ::"r"(dst),
      "l"(tm), "r"(bar), "r"(c0), "r"(c1), "h"((uint16_t)3)
      : "memory");
}
__device__ __forceinline__ void bulk_load(uint32_t dst, const void* src, uint32_t bytes, uint32_t bar) {
  asm volatile("cp.async.bulk.shared::cluster.global.mbarrier::complete_tx::bytes [%0], [%1], %2, [%3];" ::"r"(dst),
               "l"(src), "r"(bytes), "r"(bar)
               : "memory");
}
__device__ __forceinline__ void tma_store_2d(const CUtensorMap* tm, uint32_t src, int c0, int c1) {
  asm volatile("cp.async.bulk.tensor.2d.global.shared::cta.bulk_group [%0, {%2, %3}], [%1];" ::"l"(tm), "r"(src),
               "r"(c0), "r"(c1)
               : "memory");
}
__device__ __forceinline__ void wgmma_fence() { asm volatile("wgmma.fence.sync.aligned;" ::: "memory"); }
__device__ __forceinline__ void wgmma_commit() { asm volatile("wgmma.commit_group.sync.aligned;" ::: "memory"); }
template <int N>
__device__ __forceinline__ void wgmma_wait() {
  asm volatile("wgmma.wait_group.sync.aligned %0;" ::"n"(N) : "memory");
}
__device__ __forceinline__ uint64_t smem_desc(uint32_t addr) {
  return (uint64_t)((addr & 0x3FFFF) >> 4) | (1ull << 16) | (64ull << 32) | (1ull << 62);
}
__device__ __forceinline__ uint32_t bf16x2_fma(uint32_t a, uint32_t b, uint32_t c) {
  uint32_t d;
  asm("fma.rn.bf16x2 %0, %1, %2, %3;" : "=r"(d) : "r"(a), "r"(b), "r"(c));
  return d;
}
__device__ __forceinline__ uint32_t bf16x2_mul(uint32_t a, uint32_t b) {
  uint32_t d;
  asm("mul.rn.bf16x2 %0, %1, %2;" : "=r"(d) : "r"(a), "r"(b));
  return d;
}

template <int ACC>
__device__ __forceinline__ void wgmma_rs_n128(float (&d)[64], uint32_t a0, uint32_t a1, uint32_t a2, uint32_t a3,
                                              uint64_t desc_b) {
  asm volatile(
      "{\n.reg .pred p;\nsetp.ne.b32 p, %69, 0;\n"
      "wgmma.mma_async.sync.aligned.m64n128k16.f32.bf16.bf16 {"
      "%0, %1, %2, %3, %4, %5, %6, %7, %8, %9, %10, %11, %12, %13, %14, %15, "
      "%16, %17, %18, %19, %20, %21, %22, %23, %24, %25, %26, %27, %28, %29, %30, %31, "
      "%32, %33, %34, %35, %36, %37, %38, %39, %40, %41, %42, %43, %44, %45, %46, %47, "
      "%48, %49, %50, %51, %52, %53, %54, %55, %56, %57, %58, %59, %60, %61, %62, %63"
      "}, {%64, %65, %66, %67}, %68, p, 1, 1, 0;\n}\n"
      : "+f"(d[0]), "+f"(d[1]), "+f"(d[2]), "+f"(d[3]), "+f"(d[4]), "+f"(d[5]), "+f"(d[6]), "+f"(d[7]),
        "+f"(d[8]), "+f"(d[9]), "+f"(d[10]), "+f"(d[11]), "+f"(d[12]), "+f"(d[13]), "+f"(d[14]), "+f"(d[15]),
        "+f"(d[16]), "+f"(d[17]), "+f"(d[18]), "+f"(d[19]), "+f"(d[20]), "+f"(d[21]), "+f"(d[22]), "+f"(d[23]),
        "+f"(d[24]), "+f"(d[25]), "+f"(d[26]), "+f"(d[27]), "+f"(d[28]), "+f"(d[29]), "+f"(d[30]), "+f"(d[31]),
        "+f"(d[32]), "+f"(d[33]), "+f"(d[34]), "+f"(d[35]), "+f"(d[36]), "+f"(d[37]), "+f"(d[38]), "+f"(d[39]),
        "+f"(d[40]), "+f"(d[41]), "+f"(d[42]), "+f"(d[43]), "+f"(d[44]), "+f"(d[45]), "+f"(d[46]), "+f"(d[47]),
        "+f"(d[48]), "+f"(d[49]), "+f"(d[50]), "+f"(d[51]), "+f"(d[52]), "+f"(d[53]), "+f"(d[54]), "+f"(d[55]),
        "+f"(d[56]), "+f"(d[57]), "+f"(d[58]), "+f"(d[59]), "+f"(d[60]), "+f"(d[61]), "+f"(d[62]), "+f"(d[63])
      : "r"(a0), "r"(a1), "r"(a2), "r"(a3), "l"(desc_b), "n"(ACC));
}

template <int ACC>
__device__ __forceinline__ void wgmma_rs_n104(float (&d)[64], uint32_t a0, uint32_t a1, uint32_t a2, uint32_t a3,
                                              uint64_t desc_b) {
  asm volatile(
      "{\n.reg .pred p;\nsetp.ne.b32 p, %57, 0;\n"
      "wgmma.mma_async.sync.aligned.m64n104k16.f32.bf16.bf16 {"
      "%0, %1, %2, %3, %4, %5, %6, %7, %8, %9, %10, %11, %12, %13, %14, %15, "
      "%16, %17, %18, %19, %20, %21, %22, %23, %24, %25, %26, %27, %28, %29, %30, %31, "
      "%32, %33, %34, %35, %36, %37, %38, %39, %40, %41, %42, %43, %44, %45, %46, %47, "
      "%48, %49, %50, %51"
      "}, {%52, %53, %54, %55}, %56, p, 1, 1, 0;\n}\n"
      : "+f"(d[0]), "+f"(d[1]), "+f"(d[2]), "+f"(d[3]), "+f"(d[4]), "+f"(d[5]), "+f"(d[6]), "+f"(d[7]),
        "+f"(d[8]), "+f"(d[9]), "+f"(d[10]), "+f"(d[11]), "+f"(d[12]), "+f"(d[13]), "+f"(d[14]), "+f"(d[15]),
        "+f"(d[16]), "+f"(d[17]), "+f"(d[18]), "+f"(d[19]), "+f"(d[20]), "+f"(d[21]), "+f"(d[22]), "+f"(d[23]),
        "+f"(d[24]), "+f"(d[25]), "+f"(d[26]), "+f"(d[27]), "+f"(d[28]), "+f"(d[29]), "+f"(d[30]), "+f"(d[31]),
        "+f"(d[32]), "+f"(d[33]), "+f"(d[34]), "+f"(d[35]), "+f"(d[36]), "+f"(d[37]), "+f"(d[38]), "+f"(d[39]),
        "+f"(d[40]), "+f"(d[41]), "+f"(d[42]), "+f"(d[43]), "+f"(d[44]), "+f"(d[45]), "+f"(d[46]), "+f"(d[47]),
        "+f"(d[48]), "+f"(d[49]), "+f"(d[50]), "+f"(d[51])
      : "r"(a0), "r"(a1), "r"(a2), "r"(a3), "l"(desc_b), "n"(ACC));
}

template <int ACC>
__device__ __forceinline__ void wgmma_ss_n104(float (&d)[64], uint64_t desc_a, uint64_t desc_b) {
  asm volatile(
      "{\n.reg .pred p;\nsetp.ne.b32 p, %54, 0;\n"
      "wgmma.mma_async.sync.aligned.m64n104k16.f32.bf16.bf16 {"
      "%0, %1, %2, %3, %4, %5, %6, %7, %8, %9, %10, %11, %12, %13, %14, %15, "
      "%16, %17, %18, %19, %20, %21, %22, %23, %24, %25, %26, %27, %28, %29, %30, %31, "
      "%32, %33, %34, %35, %36, %37, %38, %39, %40, %41, %42, %43, %44, %45, %46, %47, "
      "%48, %49, %50, %51"
      "}, %52, %53, p, 1, 1, 1, 0;\n}\n"
      : "+f"(d[0]), "+f"(d[1]), "+f"(d[2]), "+f"(d[3]), "+f"(d[4]), "+f"(d[5]), "+f"(d[6]), "+f"(d[7]),
        "+f"(d[8]), "+f"(d[9]), "+f"(d[10]), "+f"(d[11]), "+f"(d[12]), "+f"(d[13]), "+f"(d[14]), "+f"(d[15]),
        "+f"(d[16]), "+f"(d[17]), "+f"(d[18]), "+f"(d[19]), "+f"(d[20]), "+f"(d[21]), "+f"(d[22]), "+f"(d[23]),
        "+f"(d[24]), "+f"(d[25]), "+f"(d[26]), "+f"(d[27]), "+f"(d[28]), "+f"(d[29]), "+f"(d[30]), "+f"(d[31]),
        "+f"(d[32]), "+f"(d[33]), "+f"(d[34]), "+f"(d[35]), "+f"(d[36]), "+f"(d[37]), "+f"(d[38]), "+f"(d[39]),
        "+f"(d[40]), "+f"(d[41]), "+f"(d[42]), "+f"(d[43]), "+f"(d[44]), "+f"(d[45]), "+f"(d[46]), "+f"(d[47]),
        "+f"(d[48]), "+f"(d[49]), "+f"(d[50]), "+f"(d[51])
      : "l"(desc_a), "l"(desc_b), "n"(ACC));
}

__host__ __device__ constexpr bool use_imad(int b) { return (IMASK >> b) & 1; }
struct Dq {
  uint32_t addr[5], sh[5];
  uint32_t c[2], s[2];
  int tj;
};

template <int PITCH>
__device__ __forceinline__ void dq_setup(Dq& q, uint32_t base, int phase) {
  const int lane = threadIdx.x & 31;
  q.tj = (lane & 3) - phase;
#pragma unroll
  for (int b = 0; b < 5; ++b) {
    const int e = 4 * b + q.tj + 5;
    const int o = (e * 52) >> 8;
    q.addr[b] = base + (o - 1) * PITCH;
    q.sh[b] = 6 * (e - 5 * o);
    if (use_imad(b)) asm("shr.u32 %0, 0x1000000, %1;" : "=r"(q.sh[b]) : "r"(q.sh[b]));
  }
}
__device__ __forceinline__ void dq_consts(Dq& q, int h, uint16_t z, uint16_t s) {
  if (EPS) {
    q.c[h] = bf16x2_mul((uint32_t)z * 0x10001u, 0xBC80BC80u);
    q.s[h] = EPS == 1 ? __float_as_uint(__uint_as_float((uint32_t)s << 16) * 64.f) : bf16x2_mul((uint32_t)s * 0x10001u, 0x42804280u);
    return;
  }
  q.c[h] = bf16x2_mul((uint32_t)z * 0x10001u, 0xBE00BC80u);
  q.s[h] = bf16x2_mul((uint32_t)s * 0x10001u, 0x41004280u);
}
template <int R0, int NR, int PITCH = kWPitch, int DST = R0>
__device__ __forceinline__ void dq_load(uint32_t (&a)[144], const Dq& q) {
#pragma unroll
  for (int i = R0; i < R0 + NR; ++i)
    asm volatile("ld.shared.u32 %0, [%1];"
                 : "=r"(a[i - R0 + DST])
                 : "r"(q.addr[(i >> 1) % 5] + ((i >> 1) / 5) * 4 * PITCH + (i & 1) * 32));
}
template <int R0, int NR, int DST = R0>
__device__ __forceinline__ void dq_math(uint32_t (&a)[144], const Dq& q) {
#pragma unroll
  for (int i = R0; i < R0 + NR; ++i) {
    const int u = i >> 1, h = i & 1;
    uint32_t w = a[i - R0 + DST];
    if (use_imad(u % 5)) w = __byte_perm(w * q.sh[u % 5], 0, 0x3333);
    else w = __byte_perm(w >> q.sh[u % 5], 0, 0x0000);
    w &= 0x00380007u;
    if (EPS) w = bf16x2_fma(w, 0x7D807F00u, q.c[h]);
    else w = bf16x2_mul(bf16x2_fma(w, 0x7F007F00u, q.c[h]), q.s[h]);
    if (u == 0) w = q.tj < 0 ? 0u : w;
    if (u == 71) w = q.tj > 0 ? 0u : w;
    a[i - R0 + DST] = w;
  }
}
template <int R0, int NR, int PITCH = kWPitch, int DST = R0>
__device__ __forceinline__ void dq_regs(uint32_t (&a)[144], const Dq& q) {
  dq_load<R0, NR, PITCH, DST>(a, q);
  dq_math<R0, NR, DST>(a, q);
}

template <int C>
__device__ __forceinline__ void mma_chunk(float (&d)[64], const uint32_t (&a)[144], uint64_t desc) {
  wgmma_fence();
#pragma unroll
  for (int s = 4 * C; s < 4 * C + 4; ++s) {
    if (s == 0) wgmma_rs_n128<0>(d, a[0], a[1], a[2], a[3], desc);
    else wgmma_rs_n128<1>(d, a[4 * s], a[4 * s + 1], a[4 * s + 2], a[4 * s + 3], desc + 2 * (s & 3));
  }
  wgmma_commit();
}
template <int C>
__device__ __forceinline__ void mma_chunk_extra(float (&d)[64], const uint32_t (&a)[144], uint64_t desc_a,
                                                uint64_t desc) {
  wgmma_fence();
#pragma unroll
  for (int kk = 0; kk < 4; ++kk) {
    if (C < kSS) {
      if (C == 0 && kk == 0) wgmma_ss_n104<0>(d, desc_a, desc);
      else wgmma_ss_n104<1>(d, desc_a + 128 * kk, desc + 2 * kk);
    } else {
      const int r = (16 * (C - kSS) + 4 * kk) % 144;
      wgmma_rs_n104<1>(d, a[r], a[r + 1], a[r + 2], a[r + 3], desc + 2 * kk);
    }
  }
  wgmma_commit();
}

#define BOUNDARY(I) \
  asm volatile("{\n.reg .pred p;\nsetp.ne.s32 p, %0, %1;\n@p bra.uni OK;\ntrap;\nOK:\n}" ::"r"(cx.wg), "n"((I) + 100) : "memory")
#define SPLIT2 0
#define STGATE 1
#define BND1 1
#define BND2 0

struct Ctx {
  uint32_t sb;
  uint32_t empty_dst;
  uint64_t desc;
  int wg;
  bool extra;
  int phase_e;
};

template <int G>
__device__ __forceinline__ void release(const Ctx& cx) {
  if (G + kStages >= 5 * kChunks) return;
  if ((G + kStages < 4 * kChunks || cx.extra) && (threadIdx.x & 31) < 2)
    asm volatile("mbarrier.arrive.shared::cluster.b64 _, [%0];" ::"r"(cx.empty_dst + ((G + kStages) % kStages) * 8) : "memory");
}

__device__ __forceinline__ void wg_sync(int wg) {
  if (wg == 0) asm volatile("bar.sync 3, 128;" ::: "memory");
  else asm volatile("bar.sync 4, 128;" ::: "memory");
}

template <int MODE, int T, int C>
__device__ __forceinline__ void tile_step(float (&d)[64], uint32_t (&a)[144], Dq& q, const Ctx& cx) {
  constexpr int G = T * kChunks + C, S = G % kStages;
  constexpr int lag = T == 0 ? LAG0 : T == 3 ? LAG3 : LAG1;
  const uint32_t sb = cx.sb;
  mbar_wait(sb + kBarFull + S * 8, (G / kStages) & 1);
  if (MODE != 3 && C == 0 && cx.wg == 1) asm volatile("bar.sync 1, 256;" ::: "memory");
  if (GATE && T == 3 && MODE == 0 && C == GATE && cx.wg == 1 && cx.extra) asm volatile("bar.sync 7, 256;" ::: "memory");
  TR(cx.wg, T * 11 + C);
  if (MODE == 3) mma_chunk_extra<C>(d, a, cx.desc + (kOffAx + C * 8192) / 16, cx.desc + S * (kStageBytes / 16));
  else mma_chunk<C>(d, a, cx.desc + S * (kStageBytes / 16));
  if (MODE != 3 && lag == C && cx.wg == 0) asm volatile("bar.arrive 1, 256;" ::: "memory");
  if (GATE && MODE == 2 && C == 8) asm volatile("bar.arrive 7, 256;" ::: "memory");
  if (MODE == 1 && C < 8 && kPer > 0) {
    if (BND1) BOUNDARY(C);
    if (!SPLIT1) dq_load<(kPre + C * kPer) % 144, kPer>(a, q);
    dq_math<(kPre + C * kPer) % 144, kPer>(a, q);
  }
  if (MODE == 2 && C == 0) {
    const int cole = ((threadIdx.x >> 5) & 3) * 16 + ((threadIdx.x & 31) >> 2);
    dq_setup<kWePitch>(q, sb + kOffWe - kWeRow0 * kWePitch + cole * 4, cx.phase_e);
    mbar_wait(sb + kBarW1, 0);
#pragma unroll
    for (int h = 0; h < 2; ++h) {
      uint16_t z, s;
      asm volatile("ld.shared.u16 %0, [%1];" : "=h"(z) : "r"(sb + kOffZS + (cole + 8 * h) * 2));
      asm volatile("ld.shared.u16 %0, [%1];" : "=h"(s) : "r"(sb + kOffZS + 128 + (cole + 8 * h) * 2));
      dq_consts(q, h, z, s);
    }
  }
  if (MODE == 2 && C >= 2) {
    if (BND2) BOUNDARY(30 + C);
    if (!SPLIT2) dq_load<16 * kSS + trail_end(C - 1), trail_end(C) - trail_end(C - 1), kWePitch, trail_end(C - 1)>(a, q);
    dq_math<16 * kSS + trail_end(C - 1), trail_end(C) - trail_end(C - 1), trail_end(C - 1)>(a, q);
  }
  if (C > 0 && MODE != 3) wgmma_wait<1>();
  if (MODE == 1 && SPLIT1 && C < 7 && kPer > 0) dq_load<(kPre + (C + 1) * kPer) % 144, kPer>(a, q);
  if (MODE == 2 && SPLIT2 && C >= 1 && C < 8)
    dq_load<16 * kSS + trail_end(C), trail_end(C + 1) - trail_end(C), kWePitch, trail_end(C)>(a, q);
  if (C > 0 && MODE != 3) release<G - 1>(cx);
}

template <int MODE, int T>
__device__ __forceinline__ void tile(float (&d)[64], uint32_t (&a)[144], Dq& q, Ctx& cx, uint32_t zero) {
  constexpr int N = MODE == 3 ? kNX : 128;
  cx.sb += zero;
  cx.desc += zero;
  const uint32_t sb = cx.sb;
  tile_step<MODE, T, 0>(d, a, q, cx);
  tile_step<MODE, T, 1>(d, a, q, cx);
  tile_step<MODE, T, 2>(d, a, q, cx);
  tile_step<MODE, T, 3>(d, a, q, cx);
  tile_step<MODE, T, 4>(d, a, q, cx);
  tile_step<MODE, T, 5>(d, a, q, cx);
  tile_step<MODE, T, 6>(d, a, q, cx);
  tile_step<MODE, T, 7>(d, a, q, cx);
  tile_step<MODE, T, 8>(d, a, q, cx);
  const int lane = threadIdx.x & 31, warp = (threadIdx.x >> 5) & 3;
  if (MODE == 1 && lane == 0) mbar_arrive(sb + kBarDq);
  if (T > 0) mbar_wait(sb + kBarOutFree + cx.wg * 8, (T - 1) & 1);
  wgmma_wait<0>();
#pragma unroll
  for (int i = 0; i < N / 2; ++i) asm volatile("" : "+f"(d[i])::"memory");
  if (MODE != 3) release<T * kChunks + 8>(cx);
  TR(cx.wg, T * 11 + 9);
  const uint32_t st = sb + kOffOut + cx.wg * 16384 + ((lane & 7) + ((lane >> 4) << 3)) * 128 +
                      (((warp * 2 + ((lane >> 3) & 1)) ^ (lane & 7)) << 4);
  const uint32_t e0 = MODE == 3 ? q.s[0] : cx.sc[0], e1 = MODE == 3 ? q.s[1] : cx.sc[1];
  uint32_t r[32];
  if (EPS == 1) {
#pragma unroll
    for (int i = 0; i < N / 2; ++i) d[i] *= __uint_as_float((i & 2) ? e1 : e0);
  }
#pragma unroll
  for (int i = 0; i < N / 4; ++i)
    asm("cvt.rn.bf16x2.f32 %0, %1, %2;" : "=r"(r[i]) : "f"(d[2 * i + 1]), "f"(d[2 * i]));
  if (EPS == 2 && EBND && MODE != 3) BOUNDARY(200 + T);
#pragma unroll
  for (int i = 0; i < N / 8; i += 2) {
    if (EPS == 2) {
#pragma unroll
      for (int j = 0; j < 4; ++j)
        if (2 * i + j < N / 4) r[2 * i + j] = bf16x2_mul(r[2 * i + j], (j & 1) ? e1 : e0);
    }
    if (i + 1 < N / 8) {
      asm volatile("stmatrix.sync.aligned.m8n8.x4.trans.shared.b16 [%0], {%1, %2, %3, %4};" ::"r"(st + i * 1024),
                   "r"(r[2 * i]), "r"(r[2 * i + 1]), "r"(r[2 * i + 2]), "r"(r[2 * i + 3])
                   : "memory");
      if (MODE == 3 && SPLITST && i + 2 == SPLITST / 8) {
        asm volatile("fence.proxy.async.shared::cta;" ::: "memory");
        __syncwarp();
        if (lane == 0) mbar_arrive(sb + kBarOutFull);
      }
    } else {
      asm volatile("stmatrix.sync.aligned.m8n8.x2.trans.shared.b16 [%0], {%1, %2};" ::"r"(st + i * 1024), "r"(r[2 * i]),
                   "r"(r[2 * i + 1])
                   : "memory");
    }
  }
  asm volatile("fence.proxy.async.shared::cta;" ::: "memory");
  __syncwarp();
  if (lane == 0) mbar_arrive(sb + (MODE == 3 && SPLITST ? kBarFin : kBarOutFull + cx.wg * 8));
  if (T < 4) TR(cx.wg, T * 11 + 10);
}

#define PRODUCER_START \
      const bool leader = elect_one(); \
      if (leader) { \
        TRALL(2, 56); \
_Pragma("unroll") \
        for (int i = 0; i < kStages; ++i) mbar_init(sb + kBarFull + 8 * i, 1); \
        asm volatile("fence.mbarrier_init.release.cluster;" ::: "memory"); \
        TRALL(2, 57); \
      } \
      __syncwarp(); \
      asm volatile("barrier.cluster.arrive.relaxed.aligned;" ::: "memory"); \
      asm volatile("barrier.cluster.wait.aligned;" ::: "memory"); \
      if (leader) { \
        TRALL(2, 59); \
        if (X0DLY) { uint32_t ta, tb; asm volatile("mov.u32 %0, %clock;" : "=r"(ta)); do { asm volatile("mov.u32 %0, %clock;" : "=r"(tb)); } while (tb - ta < X0DLY); } \
        mbar_expect_tx(sb + kBarFull, kStageBytes); \
        tma_load_2d_mc(sb + rank * 8192, &tm_x64, sb + kBarFull, phase * 568, rank * 64); \
        TRALL(2, 0); \
_Pragma("unroll") \
        for (int i = 0; i < kStages; ++i) mbar_init(sb + kBarEmpty + 8 * i, 16); \
        mbar_init(sb + kBarW1, 1); \
        mbar_init(sb + kBarDq, 8); \
        mbar_init(sb + kBarAx, 2); \
        mbar_init(sb + kBarLd, 1); \
        mbar_init(sb + kBarFin, 4); \
        mbar_init(sb + kBarOutFull, 4); \
        mbar_init(sb + kBarOutFull + 8, 4); \
        mbar_init(sb + kBarOutFree, 1); \
        mbar_init(sb + kBarOutFree + 8, 1); \
        asm volatile("fence.mbarrier_init.release.cluster;" ::: "memory"); \
      } \
      asm volatile("mov.u32 %0, %clock;" : "=r"(t0)); \
      __syncwarp(); \
      asm volatile("bar.arrive 2, 288;" ::: "memory"); \
      asm volatile("bar.arrive 5, 128;" ::: "memory");

__global__ void __cluster_dims__(2, 1, 1) __launch_bounds__(384, 1)
    gptq_gemm_kernel(const uint32_t* __restrict__ qw, const __nv_bfloat16* __restrict__ scales,
                     const __nv_bfloat16* __restrict__ zeros, const __nv_bfloat16* __restrict__ x,
                     const uint32_t zero,
                     const __grid_constant__ CUtensorMap tm_x64, const __grid_constant__ CUtensorMap tm_w,
                     const __grid_constant__ CUtensorMap tm_o128, const __grid_constant__ CUtensorMap tm_x52,
                     const __grid_constant__ CUtensorMap tm_o104, const __grid_constant__ CUtensorMap tm_we,
                     const __grid_constant__ CUtensorMap tm_o2) {
  extern __shared__ __align__(1024) uint8_t smem[];
  const uint32_t sb = (uint32_t)__cvta_generic_to_shared(smem);
  const int cid = blockIdx.x >> 1, rank = blockIdx.x & 1;
  const int phase = cid & 3, n_own = (cid >> 2) * 256 + rank * 128;
  uint16_t z0, z1, s0, s1;
  uint32_t t0;
  const int warp_id = __shfl_sync(0xffffffffu, (int)(threadIdx.x >> 5), 0);
#define IS_CONS (warp_id < 8)
#define IS_PROD (warp_id == 8)

  if (IS_CONS) {
    asm volatile("barrier.cluster.arrive.relaxed.aligned;" ::: "memory");
    const uint32_t tid = threadIdx.x, r = (tid >> 4) & 7, c4 = (tid & 15) + ((tid >> 3) & 16);
    const uint32_t* src = qw + (r * kF + n_own + c4 * 4);
    const uint32_t dst = sb + kOffW + r * kWPitch + c4 * 16;
    if (W1DLY && tid >= 128) {
      uint32_t ta, tb;
      asm volatile("mov.u32 %0, %clock;" : "=r"(ta));
      do { asm volatile("mov.u32 %0, %clock;" : "=r"(tb)); } while (tb - ta < W1DLY);
    }
#pragma unroll
    for (int i = 0; i < kFirst; ++i) {
      asm volatile("cp.async.cg.shared.global [%0], [%1], 16;" ::"r"(dst + i * 8 * kWPitch), "l"(src + i * 8 * kF)
                   : "memory");
      if (i == G0 - 1) {
        asm volatile("cp.async.commit_group;" ::: "memory");
        TR(tid >> 7, 59);
        const uint32_t cz = n_own + (tid >> 5) * 16 + ((tid & 31) >> 2);
        const uint16_t* zp = reinterpret_cast<const uint16_t*>(zeros) + cz;
        const uint16_t* sp = reinterpret_cast<const uint16_t*>(scales) + cz;
        asm volatile("ld.global.nc.u16 %0, [%1];" : "=h"(z0) : "l"(zp));
        asm volatile("ld.global.nc.u16 %0, [%1+16];" : "=h"(z1) : "l"(zp));
        asm volatile("ld.global.nc.u16 %0, [%1];" : "=h"(s0) : "l"(sp));
        asm volatile("ld.global.nc.u16 %0, [%1+16];" : "=h"(s1) : "l"(sp));
      }
    }
    asm volatile("cp.async.commit_group;" ::: "memory");
  } else if (NEAR && IS_PROD) {
    PRODUCER_START
  } else if (NEAR || !IS_PROD) {
    asm volatile("barrier.cluster.arrive.relaxed.aligned;" ::: "memory");
    asm volatile("prefetch.tensormap [%0];" ::"l"(&tm_x64) : "memory");
  }
  const int wg = warp_id >> 2;
  const int lane = threadIdx.x & 31;
  const int col = warp_id * 16 + (lane >> 2);

  const bool has_extra = cid < kExtraClusters;
  const int ue = kClusters + cid / 10;
  const int phase_e = ue & 3, n_e = (ue >> 2) * 256 + ((cid / 5) & 1) * 128 + rank * 64, row_e = (cid % 5) * kNX;

  if (wg == 2) {
    asm volatile("setmaxnreg.dec.sync.aligned.u32 24;");
    if (warp_id == 8) {
      if (!NEAR) {
        PRODUCER_START
      }
      const bool leader = elect_one();
      if (leader) {
#pragma unroll
        for (int g = 1; g < kStages; ++g) {
          const uint32_t full = sb + kBarFull + g * 8;
          uint32_t t;
          do { asm volatile("mov.u32 %0, %clock;" : "=r"(t)); } while (t - t0 < (g <= NFAST ? g * PACE0 : NFAST * PACE0 + (g - NFAST) * PACE));
          TRALL(2, g);
          uint32_t bytes = kStageBytes;
#pragma unroll
          for (int p = kFirst; p < 8; ++p)
            if (need_step(p) == g) bytes += p < 7 ? 8 * kWPitch : 512;
          mbar_expect_tx(full, bytes);
          tma_load_2d_mc(sb + g * kStageBytes + rank * 8192, &tm_x64, full, phase * 568 + (g % kChunks) * 64,
                         rank * 64 + (g / kChunks) * 128);
#pragma unroll
          for (int p = kFirst; p < 8; ++p)
            if (need_step(p) == g) {
              if (p < 7) tma_load_2d(sb + kOffW + p * 8 * kWPitch, &tm_w, full, n_own, p * 8);
              else bulk_load(sb + kOffW + 56 * kWPitch, qw + 56 * kF + n_own, 512, full);
            }
        }
        const int total = has_extra ? 5 * kChunks : 4 * kChunks;
        int c = kStages % kChunks, row = rank * 64 + (kStages / kChunks) * 128;
        uint32_t stage = 0, parity = 0;
#pragma unroll 1
        for (int g = kStages; g < total; ++g) {
          const uint32_t full = sb + kBarFull + stage * 8, dst = sb + stage * kStageBytes;
          mbar_wait_lazy(sb + kBarEmpty + stage * 8, parity);
          TRALL(2, g);
          if (g < 4 * kChunks) {
            mbar_expect_tx(full, kStageBytes);
            tma_load_2d_mc(dst + rank * 8192, &tm_x64, full, phase * 568 + c * 64, row);
          } else {
            mbar_expect_tx(full, kNX * 128);
            tma_load_2d_mc(dst + rank * (kNX * 64), &tm_x52, full, phase_e * 568 + c * 64, row_e + rank * (kNX / 2));
          }
          if (++c == kChunks) { c = 0; row += 128; }
          if (++stage == kStages) { stage = 0; parity ^= 1; }
        }
        if (STGATE) mbar_arrive(sb + kBarLd);
      }
    } else if (warp_id == 9) {
      asm volatile("prefetch.tensormap [%0];" ::"l"(&tm_w) : "memory");
      asm volatile("bar.sync 5, 128;" ::: "memory");
      if (elect_one()) {
        const int nst = has_extra ? 9 : 8;
#pragma unroll 1
        for (int i = 0; i < nst; ++i) {
          const int w = i & 1, t = i >> 1;
          if (i >= 7) mbar_wait(sb + kBarOutFull + w * 8, t & 1);
          else mbar_wait_lazy(sb + kBarOutFull + w * 8, t & 1);
          if (STGATE && i == 6) mbar_wait_lazy(sb + kBarLd, 0);
          TRALL(3, 2 * i);
          if (i < 8) tma_store_2d(&tm_o128, sb + kOffOut + w * 16384, phase * kF + n_own + w * 64, t * 128);
          else tma_store_2d(&tm_o104, sb + kOffOut, phase_e * kF + n_e, row_e);
          if (SPLITST && i == 8) {
            mbar_wait(sb + kBarFin, 0);
            tma_store_2d(&tm_o2, sb + kOffOut + SPLITST * 128, phase_e * kF + n_e, row_e + SPLITST);
          }
          asm volatile("cp.async.bulk.commit_group;" ::: "memory");
          if (i < 7) {
            asm volatile("cp.async.bulk.wait_group.read 0;" ::: "memory");
            mbar_arrive(sb + kBarOutFree + w * 8);
          }
          TRALL(3, 2 * i + 1);
        }
        asm volatile("cp.async.bulk.wait_group.read 0;" ::: "memory");
      }
    } else {
      asm volatile("bar.sync 5, 128;" ::: "memory");
      if (has_extra) {
        const int h = threadIdx.x - 320, c4 = h & 15;
        const int colx = n_e + c4 * 4;
        mbar_wait_lazy(sb + kBarDq, 0);
        TR(3, 32 + (warp_id & 1));
        if (warp_id == 11 && elect_one()) {
          mbar_expect_tx(sb + kBarW1, kWeRows * kWePitch + 256);
          tma_load_2d(sb + kOffWe, &tm_we, sb + kBarW1, n_e, kWeRow0);
          bulk_load(sb + kOffZS, zeros + n_e, 128, sb + kBarW1);
          bulk_load(sb + kOffZS + 128, scales + n_e, 128, sb + kBarW1);
        }
        __syncwarp();
        uint32_t src = sb + kOffHead + (h >> 4) * 256 + c4 * 16;
#pragma unroll
        for (int i = 0; i < (kHeadRows + 3) / 4; ++i)
          if (4 * i + 3 < kHeadRows || 4 * i + (h >> 4) < kHeadRows)
            asm volatile("cp.async.cg.shared.global [%0], [%1], 16;" ::"r"(src + i * 1024),
                         "l"(qw + ((h >> 4) + 4 * i) * kF + colx)
                         : "memory");
        uint32_t c[2], s[2];
        {
          const uint2 z2 = __ldg(reinterpret_cast<const uint2*>(zeros + colx));
          const uint2 s2 = __ldg(reinterpret_cast<const uint2*>(scales + colx));
          c[0] = bf16x2_mul(z2.x, 0xBC80BC80u); c[1] = bf16x2_mul(z2.y, 0xBC80BC80u);
          s[0] = bf16x2_mul(s2.x, 0x42804280u); s[1] = bf16x2_mul(s2.y, 0x42804280u);
        }
        if (h < 16 * phase_e)
          asm volatile("st.shared.v4.u32 [%0], {%1, %1, %1, %1};" ::"r"(sb + kOffAx + h * 16), "r"(0u) : "memory");
        uint32_t row = sb + kOffAx + (10 * (h >> 4) + 2 * phase_e) * 128 + c4 * 8;
        const uint32_t src_end = sb + kOffHead + kHeadRows * 256;
        asm volatile("cp.async.wait_all;" ::: "memory");
#pragma unroll 1
        for (; src < src_end; src += 1024, row += 40 * 128) {
          uint4 w;
          asm volatile("ld.shared.v4.u32 {%0, %1, %2, %3}, [%4];"
                       : "=r"(w.x), "=r"(w.y), "=r"(w.z), "=r"(w.w)
                       : "r"(src)
                       : "memory");
          uint32_t win[2], ad;
#pragma unroll
          for (int i = 0; i < 10; ++i) {
            constexpr uint32_t sel[4] = {0x5410, 0x6521, 0x7632, 0x7733};
            constexpr int pos[10] = {0, 3, 2, 1, 4, 3, 2, 5, 0, 3};
            if (i == 0 || i == 3 || i == 6 || i == 8) {
              const uint32_t se = sel[i == 0 ? 0 : i == 3 ? 1 : i == 6 ? 2 : 3];
              win[0] = __byte_perm(w.x, w.y, se);
              win[1] = __byte_perm(w.z, w.w, se);
            }
            uint32_t v[2];
#pragma unroll
            for (int j = 0; j < 2; ++j) {
              const uint32_t f = ((i == 2 || i == 5) ? win[j] >> 4 : win[j]) & (0x00070007u << pos[i]);
              v[j] = bf16x2_fma(f, 0x7F007F00u - pos[i] * 0x00800080u, c[j]);
              if (!EPS) v[j] = bf16x2_mul(v[j], s[j]);
            }
            if ((i & 1) == 0) {
              asm volatile("{\n.reg .u32 t;\nadd.u32 %0, %1, %2;\nshr.u32 t, %0, 3;\nlop3.b32 %0, %0, t, 0x70, 0x78;\n}"
                           : "=r"(ad)
                           : "r"(row), "r"(i * 128));
              asm volatile("st.shared.v2.u32 [%0], {%1, %2};" ::"r"(ad), "r"(v[0]), "r"(v[1]) : "memory");
            } else {
              asm volatile("st.shared.v2.u32 [%0+128], {%1, %2};" ::"r"(ad ^ 16), "r"(v[0]), "r"(v[1]) : "memory");
            }
          }
        }
        asm volatile("fence.proxy.async.shared::cta;" ::: "memory");
        __syncwarp();
        if (lane == 0) mbar_arrive(sb + kBarAx);
        TR(3, 34 + (warp_id & 1));
      }
    }
  } else {
    TR(wg, 54);
    asm volatile("setmaxnreg.inc.sync.aligned.u32 240;");
    Ctx cx;
    cx.sb = sb;
    cx.wg = wg;
    cx.extra = has_extra;
    cx.phase_e = phase_e;
    cx.desc = smem_desc(sb);
    asm("mapa.shared::cluster.u32 %0, %1, %2;" : "=r"(cx.empty_dst) : "r"(sb + kBarEmpty), "r"(lane & 1));
    float d[64];
    uint32_t a[144];
    Dq q;
    dq_setup<kWPitch>(q, sb + kOffW + col * 4, phase);
    dq_consts(q, 0, z0, s0);
    dq_consts(q, 1, z1, s1);
    cx.sc[0] = q.s[0];
    cx.sc[1] = q.s[1];
    if (PIN) {
      uint32_t x = (q.addr[0] ^ q.addr[1] ^ q.addr[2]) + (q.addr[3] ^ q.addr[4] ^ q.sh[0]) + (q.sh[1] ^ q.sh[2] ^ q.sh[3]) +
                   (q.sh[4] ^ cx.empty_dst);
      if (PIN == 2) x += (q.c[0] ^ q.c[1] ^ q.s[0]) + q.s[1];
      asm volatile("{\n.reg .pred p;\n.reg .u32 t;\nand.b32 t, %0, %1;\nsetp.eq.u32 p, t, 0;\n@p bra OK;\ntrap;\nOK:\n}" ::"r"(x), "r"(zero) : "memory");
    }
    constexpr int kBlk = G0 == 1 ? 16 : (20 * G0 < kPre ? 20 * G0 : kPre);
    asm volatile("cp.async.wait_group 1;" ::: "memory");
    wg_sync(wg);
    TR(wg, 58);
    dq_regs<0, kBlk>(a, q);
    asm volatile("cp.async.wait_group 0;" ::: "memory");
    wg_sync(wg);
    TR(wg, 57);
    if (kPre > kBlk) dq_regs<kBlk % 144, kPre - kBlk>(a, q);
    if (SPLIT1 && kPer > 0) dq_load<kPre % 144, kPer>(a, q);
    TR(wg, 56);
    asm volatile("bar.sync 2, 288;" ::: "memory");
    TR(wg, 55);
    tile<1, 0>(d, a, q, cx, zero);
    tile<0, 1>(d, a, q, cx, zero);
    tile<0, 2>(d, a, q, cx, zero);
    if (wg == 0 && has_extra) {
      tile<2, 3>(d, a, q, cx, zero);
      mbar_wait(sb + kBarAx, 0);
      tile<3, 4>(d, a, q, cx, zero);
    } else {
      tile<0, 3>(d, a, q, cx, zero);
    }
  }
}

typedef CUresult (*EncodeFn)(CUtensorMap*, CUtensorMapDataType, cuuint32_t, void*, const cuuint64_t*,
                             const cuuint64_t*, const cuuint32_t*, const cuuint32_t*, CUtensorMapInterleave,
                             CUtensorMapSwizzle, CUtensorMapL2promotion, CUtensorMapFloatOOBfill);

void make_map(EncodeFn enc, CUtensorMap* tm, CUtensorMapDataType dt, const void* base, uint64_t d0, uint64_t d1,
              uint64_t stride, uint32_t b0, uint32_t b1, CUtensorMapSwizzle sw, CUtensorMapL2promotion promo) {
  cuuint64_t dims[2] = {d0, d1};
  cuuint64_t strides[1] = {stride};
  cuuint32_t box[2] = {b0, b1};
  cuuint32_t es[2] = {1, 1};
  enc(tm, dt, 2, const_cast<void*>(base), dims, strides, box, es, CU_TENSOR_MAP_INTERLEAVE_NONE, sw, promo,
      CU_TENSOR_MAP_FLOAT_OOB_FILL_NONE);
}

}

extern "C" void kernel_launch(void* const* d_in, const int* in_sizes, int n_in, void* d_out, int out_size) {
  (void)in_sizes; (void)n_in; (void)out_size;
  static EncodeFn enc = nullptr;
  if (!enc) {
    void* fn = nullptr;
    cudaDriverEntryPointQueryResult qr;
    cudaGetDriverEntryPoint("cuTensorMapEncodeTiled", &fn, cudaEnableDefault, &qr);
    enc = (EncodeFn)fn;
    cudaFuncSetAttribute(gptq_gemm_kernel, cudaFuncAttributeMaxDynamicSharedMemorySize, kSmemBytes);
  }
  CUtensorMap x64, x52, w, we, o128, o104, o2;
  make_map(enc, &x64, CU_TENSOR_MAP_DATA_TYPE_BFLOAT16, d_in[0], 2280, kSup, 4560, 64, 64, CU_TENSOR_MAP_SWIZZLE_128B,
           (CUtensorMapL2promotion)XPROMO);
  make_map(enc, &x52, CU_TENSOR_MAP_DATA_TYPE_BFLOAT16, d_in[0], 2280, kSup, 4560, 64, kNX / 2,
           CU_TENSOR_MAP_SWIZZLE_128B, CU_TENSOR_MAP_L2_PROMOTION_L2_128B);
  make_map(enc, &w, CU_TENSOR_MAP_DATA_TYPE_INT32, d_in[1], kF, 57, kF * 4, 136, 8, CU_TENSOR_MAP_SWIZZLE_NONE,
           (CUtensorMapL2promotion)WPROMO);
  make_map(enc, &we, CU_TENSOR_MAP_DATA_TYPE_INT32, d_in[1], kF, 57, kF * 4, 72, kWeRows, CU_TENSOR_MAP_SWIZZLE_NONE,
           CU_TENSOR_MAP_L2_PROMOTION_L2_128B);
  make_map(enc, &o128, CU_TENSOR_MAP_DATA_TYPE_BFLOAT16, d_out, 4 * kF, kSup, 8 * kF, 64, 128,
           CU_TENSOR_MAP_SWIZZLE_128B, CU_TENSOR_MAP_L2_PROMOTION_NONE);
  make_map(enc, &o104, CU_TENSOR_MAP_DATA_TYPE_BFLOAT16, d_out, 4 * kF, kSup, 8 * kF, 64, SPLITST ? SPLITST : kNX,
           CU_TENSOR_MAP_SWIZZLE_128B, CU_TENSOR_MAP_L2_PROMOTION_NONE);
  make_map(enc, &o2, CU_TENSOR_MAP_DATA_TYPE_BFLOAT16, d_out, 4 * kF, kSup, 8 * kF, 64, kNX - SPLITST,
           CU_TENSOR_MAP_SWIZZLE_128B, CU_TENSOR_MAP_L2_PROMOTION_NONE);
  gptq_gemm_kernel<<<2 * kClusters, 384, kSmemBytes>>>((const uint32_t*)d_in[1], (const __nv_bfloat16*)d_in[2],
                                                       (const __nv_bfloat16*)d_in[3], (const __nv_bfloat16*)d_in[0], 0u, x64, w, o128, x52, o104, we, o2);
}
```

```cpp
#include <cuda.h>
#include <cuda_bf16.h>
#include <cuda_runtime.h>
#include <stdint.h>

namespace {

constexpr int kF = 4608;
constexpr int kSup = 512;
constexpr int kChunks = 9;
constexpr int kNX = 104;
constexpr int kClusters = 66;
constexpr int kExtraClusters = 60;

constexpr int kPre = 32;
constexpr int kLagFirst = 2;
constexpr int kLagMid = 4;
constexpr int kLagLast = 3;
constexpr int kGate = 5;
constexpr int kPaceFirst = 250;
constexpr int kPace = 400;
constexpr int kSS = 2;
constexpr int kRefillFirst = 3;

constexpr int kStages = 10;
constexpr int kStageBytes = 16384;
constexpr int kWPitch = 544;
constexpr int kWePitch = 288;
constexpr int kHeadRows = (64 * kSS + 9) / 10;
constexpr int kWeRow0 = (32 * kSS - 3) / 5;
constexpr int kWeRows = 57 - kWeRow0;
constexpr int kOffOut = kStages * kStageBytes;
constexpr int kOffW = kOffOut + 2 * 16384;
constexpr int kOffAx = kOffW;
constexpr int kOffWe = kOffAx + (10 * kHeadRows + 6) * 128;
constexpr int kOffHead = kOffWe + (kWeRows + 1) * kWePitch;
constexpr int kOffZS = kOffHead + kHeadRows * 256;
constexpr int kBarFull = kOffZS + 256;
constexpr int kBarEmpty = kBarFull + 8 * kStages;
constexpr int kBarWe = kBarEmpty + 8 * kStages;
constexpr int kBarDq = kBarWe + 8;
constexpr int kBarAx = kBarDq + 8;
constexpr int kBarLd = kBarAx + 8;
constexpr int kBarOutFull = kBarLd + 8;
constexpr int kBarOutFree = kBarOutFull + 16;
constexpr int kOffEnd = kBarOutFree + 16;
static_assert(kBarFull >= kOffW + 58 * kWPitch, "barriers must stay clear of the packed slab");

__host__ __device__ constexpr int head_end(int c) { return c >= 8 ? 144 : kPre + ((144 - kPre) * c + 15) / 16 * 2; }
__host__ __device__ constexpr int last_word(int regs) { return (2 * regs - 1) / 5 > 56 ? 56 : (2 * regs - 1) / 5; }
constexpr int kFirst = last_word(head_end(2)) / 8 + 1;
__host__ __device__ constexpr int ride_step(int p) {
  int c = 0;
  while (c < 8 && last_word(head_end(c + 2)) < 8 * p) ++c;
  return c;
}
__host__ __device__ constexpr int refill_end(int c) {
  constexpr int total = 16 * (kChunks - kSS), steps = kChunks - kRefillFirst;
  return c < kRefillFirst ? 0 : c >= 8 ? total : ((total * (c - kRefillFirst + 1) + 2 * steps - 1) / (2 * steps)) * 2;
}
static_assert(kFirst == 3 && last_word(kPre) < 16, "front groups");

constexpr int kSmemBytes = kOffEnd;
static_assert(kSmemBytes <= 232448, "smem");

__device__ __forceinline__ void mbar_init(uint32_t bar, uint32_t cnt) {
  asm volatile("mbarrier.init.shared::cta.b64 [%0], %1;" ::"r"(bar), "r"(cnt) : "memory");
}
__device__ __forceinline__ void mbar_expect_tx(uint32_t bar, uint32_t bytes) {
  asm volatile("mbarrier.arrive.expect_tx.shared::cta.b64 _, [%0], %1;" ::"r"(bar), "r"(bytes) : "memory");
}
__device__ __forceinline__ void mbar_arrive(uint32_t bar) {
  asm volatile("mbarrier.arrive.shared::cta.b64 _, [%0];" ::"r"(bar) : "memory");
}
__device__ __forceinline__ void mbar_wait(uint32_t bar, uint32_t parity) {
  asm volatile(
      "{\n.reg .pred p;\n.reg .u32 it;\n"
      "mbarrier.try_wait.parity.shared::cta.b64 p, [%0], %1;\n"
      "@p bra DONE;\n"
      "mov.u32 it, 0;\n"
      "SPIN:\n"
      "mbarrier.try_wait.parity.shared::cta.b64 p, [%0], %1;\n"
      "@p bra DONE;\n"
      "add.u32 it, it, 1;\n"
      "setp.lt.u32 p, it, 0x100000;\n"
      "@p bra SPIN;\n"
      "trap;\n"
      "DONE:\n}" ::"r"(bar),
      "r"(parity)
      : "memory");
}
__device__ __forceinline__ void mbar_wait_lazy(uint32_t bar, uint32_t parity) {
  asm volatile(
      "{\n.reg .pred p;\n.reg .u32 it;\n"
      "mov.u32 it, 0;\n"
      "SPIN:\n"
      "mbarrier.try_wait.parity.shared::cta.b64 p, [%0], %1, 4000;\n"
      "@p bra DONE;\n"
      "add.u32 it, it, 1;\n"
      "setp.lt.u32 p, it, 0x40000;\n"
      "@p bra SPIN;\n"
      "trap;\n"
      "DONE:\n}" ::"r"(bar),
      "r"(parity)
      : "memory");
}
__device__ __forceinline__ bool elect_one() {
  uint32_t p;
  asm volatile("{\n.reg .pred q;\nelect.sync _|q, 0xffffffff;\nselp.u32 %0, 1, 0, q;\n}" : "=r"(p));
  return p;
}
__device__ __forceinline__ void tma_load_2d(uint32_t dst, const CUtensorMap* tm, uint32_t bar, int c0, int c1) {
  asm volatile(
      "cp.async.bulk.tensor.2d.shared::cluster.global.mbarrier::complete_tx::bytes [%0], [%1, {%3, %4}], [%2];" ::"r"(dst),
      "l"(tm), "r"(bar), "r"(c0), "r"(c1)
      : "memory");
}
__device__ __forceinline__ void tma_load_2d_mc(uint32_t dst, const CUtensorMap* tm, uint32_t bar, int c0, int c1) {
  asm volatile(
      "cp.async.bulk.tensor.2d.shared::cluster.global.mbarrier::complete_tx::bytes.multicast::cluster [%0], [%1, {%3, "
      "%4}], [%2], %5;" ::"r"(dst),
      "l"(tm), "r"(bar), "r"(c0), "r"(c1), "h"((uint16_t)3)
      : "memory");
}
__device__ __forceinline__ void bulk_load(uint32_t dst, const void* src, uint32_t bytes, uint32_t bar) {
  asm volatile("cp.async.bulk.shared::cluster.global.mbarrier::complete_tx::bytes [%0], [%1], %2, [%3];" ::"r"(dst),
               "l"(src), "r"(bytes), "r"(bar)
               : "memory");
}
__device__ __forceinline__ void tma_store_2d(const CUtensorMap* tm, uint32_t src, int c0, int c1) {
  asm volatile("cp.async.bulk.tensor.2d.global.shared::cta.bulk_group [%0, {%2, %3}], [%1];" ::"l"(tm), "r"(src),
               "r"(c0), "r"(c1)
               : "memory");
}
__device__ __forceinline__ void cp_async16(uint32_t dst, const void* src) {
  asm volatile("cp.async.cg.shared.global [%0], [%1], 16;" ::"r"(dst), "l"(src) : "memory");
}
__device__ __forceinline__ uint16_t lds_u16(uint32_t addr) {
  uint16_t v;
  asm volatile("ld.shared.u16 %0, [%1];" : "=h"(v) : "r"(addr));
  return v;
}
__device__ __forceinline__ void wgmma_fence() { asm volatile("wgmma.fence.sync.aligned;" ::: "memory"); }
__device__ __forceinline__ void wgmma_commit() { asm volatile("wgmma.commit_group.sync.aligned;" ::: "memory"); }
template <int N>
__device__ __forceinline__ void wgmma_wait() {
  asm volatile("wgmma.wait_group.sync.aligned %0;" ::"n"(N) : "memory");
}
__device__ __forceinline__ uint64_t smem_desc(uint32_t addr) {
  return (uint64_t)((addr & 0x3FFFF) >> 4) | (1ull << 16) | (64ull << 32) | (1ull << 62);
}
__device__ __forceinline__ uint32_t bf16x2_fma(uint32_t a, uint32_t b, uint32_t c) {
  uint32_t d;
  asm("fma.rn.bf16x2 %0, %1, %2, %3;" : "=r"(d) : "r"(a), "r"(b), "r"(c));
  return d;
}
__device__ __forceinline__ uint32_t bf16x2_mul(uint32_t a, uint32_t b) {
  uint32_t d;
  asm("mul.rn.bf16x2 %0, %1, %2;" : "=r"(d) : "r"(a), "r"(b));
  return d;
}

template <int ACC>
__device__ __forceinline__ void wgmma_rs_n128(float (&d)[64], uint32_t a0, uint32_t a1, uint32_t a2, uint32_t a3,
                                              uint64_t desc_b) {
  asm volatile(
      "{\n.reg .pred p;\nsetp.ne.b32 p, %69, 0;\n"
      "wgmma.mma_async.sync.aligned.m64n128k16.f32.bf16.bf16 {"
      "%0, %1, %2, %3, %4, %5, %6, %7, %8, %9, %10, %11, %12, %13, %14, %15, "
      "%16, %17, %18, %19, %20, %21, %22, %23, %24, %25, %26, %27, %28, %29, %30, %31, "
      "%32, %33, %34, %35, %36, %37, %38, %39, %40, %41, %42, %43, %44, %45, %46, %47, "
      "%48, %49, %50, %51, %52, %53, %54, %55, %56, %57, %58, %59, %60, %61, %62, %63"
      "}, {%64, %65, %66, %67}, %68, p, 1, 1, 0;\n}\n"
      : "+f"(d[0]), "+f"(d[1]), "+f"(d[2]), "+f"(d[3]), "+f"(d[4]), "+f"(d[5]), "+f"(d[6]), "+f"(d[7]),
        "+f"(d[8]), "+f"(d[9]), "+f"(d[10]), "+f"(d[11]), "+f"(d[12]), "+f"(d[13]), "+f"(d[14]), "+f"(d[15]),
        "+f"(d[16]), "+f"(d[17]), "+f"(d[18]), "+f"(d[19]), "+f"(d[20]), "+f"(d[21]), "+f"(d[22]), "+f"(d[23]),
        "+f"(d[24]), "+f"(d[25]), "+f"(d[26]), "+f"(d[27]), "+f"(d[28]), "+f"(d[29]), "+f"(d[30]), "+f"(d[31]),
        "+f"(d[32]), "+f"(d[33]), "+f"(d[34]), "+f"(d[35]), "+f"(d[36]), "+f"(d[37]), "+f"(d[38]), "+f"(d[39]),
        "+f"(d[40]), "+f"(d[41]), "+f"(d[42]), "+f"(d[43]), "+f"(d[44]), "+f"(d[45]), "+f"(d[46]), "+f"(d[47]),
        "+f"(d[48]), "+f"(d[49]), "+f"(d[50]), "+f"(d[51]), "+f"(d[52]), "+f"(d[53]), "+f"(d[54]), "+f"(d[55]),
        "+f"(d[56]), "+f"(d[57]), "+f"(d[58]), "+f"(d[59]), "+f"(d[60]), "+f"(d[61]), "+f"(d[62]), "+f"(d[63])
      : "r"(a0), "r"(a1), "r"(a2), "r"(a3), "l"(desc_b), "n"(ACC));
}

template <int ACC>
__device__ __forceinline__ void wgmma_rs_n104(float (&d)[64], uint32_t a0, uint32_t a1, uint32_t a2, uint32_t a3,
                                              uint64_t desc_b) {
  asm volatile(
      "{\n.reg .pred p;\nsetp.ne.b32 p, %57, 0;\n"
      "wgmma.mma_async.sync.aligned.m64n104k16.f32.bf16.bf16 {"
      "%0, %1, %2, %3, %4, %5, %6, %7, %8, %9, %10, %11, %12, %13, %14, %15, "
      "%16, %17, %18, %19, %20, %21, %22, %23, %24, %25, %26, %27, %28, %29, %30, %31, "
      "%32, %33, %34, %35, %36, %37, %38, %39, %40, %41, %42, %43, %44, %45, %46, %47, "
      "%48, %49, %50, %51"
      "}, {%52, %53, %54, %55}, %56, p, 1, 1, 0;\n}\n"
      : "+f"(d[0]), "+f"(d[1]), "+f"(d[2]), "+f"(d[3]), "+f"(d[4]), "+f"(d[5]), "+f"(d[6]), "+f"(d[7]),
        "+f"(d[8]), "+f"(d[9]), "+f"(d[10]), "+f"(d[11]), "+f"(d[12]), "+f"(d[13]), "+f"(d[14]), "+f"(d[15]),
        "+f"(d[16]), "+f"(d[17]), "+f"(d[18]), "+f"(d[19]), "+f"(d[20]), "+f"(d[21]), "+f"(d[22]), "+f"(d[23]),
        "+f"(d[24]), "+f"(d[25]), "+f"(d[26]), "+f"(d[27]), "+f"(d[28]), "+f"(d[29]), "+f"(d[30]), "+f"(d[31]),
        "+f"(d[32]), "+f"(d[33]), "+f"(d[34]), "+f"(d[35]), "+f"(d[36]), "+f"(d[37]), "+f"(d[38]), "+f"(d[39]),
        "+f"(d[40]), "+f"(d[41]), "+f"(d[42]), "+f"(d[43]), "+f"(d[44]), "+f"(d[45]), "+f"(d[46]), "+f"(d[47]),
        "+f"(d[48]), "+f"(d[49]), "+f"(d[50]), "+f"(d[51])
      : "r"(a0), "r"(a1), "r"(a2), "r"(a3), "l"(desc_b), "n"(ACC));
}

template <int ACC>
__device__ __forceinline__ void wgmma_ss_n104(float (&d)[64], uint64_t desc_a, uint64_t desc_b) {
  asm volatile(
      "{\n.reg .pred p;\nsetp.ne.b32 p, %54, 0;\n"
      "wgmma.mma_async.sync.aligned.m64n104k16.f32.bf16.bf16 {"
      "%0, %1, %2, %3, %4, %5, %6, %7, %8, %9, %10, %11, %12, %13, %14, %15, "
      "%16, %17, %18, %19, %20, %21, %22, %23, %24, %25, %26, %27, %28, %29, %30, %31, "
      "%32, %33, %34, %35, %36, %37, %38, %39, %40, %41, %42, %43, %44, %45, %46, %47, "
      "%48, %49, %50, %51"
      "}, %52, %53, p, 1, 1, 1, 0;\n}\n"
      : "+f"(d[0]), "+f"(d[1]), "+f"(d[2]), "+f"(d[3]), "+f"(d[4]), "+f"(d[5]), "+f"(d[6]), "+f"(d[7]),
        "+f"(d[8]), "+f"(d[9]), "+f"(d[10]), "+f"(d[11]), "+f"(d[12]), "+f"(d[13]), "+f"(d[14]), "+f"(d[15]),
        "+f"(d[16]), "+f"(d[17]), "+f"(d[18]), "+f"(d[19]), "+f"(d[20]), "+f"(d[21]), "+f"(d[22]), "+f"(d[23]),
        "+f"(d[24]), "+f"(d[25]), "+f"(d[26]), "+f"(d[27]), "+f"(d[28]), "+f"(d[29]), "+f"(d[30]), "+f"(d[31]),
        "+f"(d[32]), "+f"(d[33]), "+f"(d[34]), "+f"(d[35]), "+f"(d[36]), "+f"(d[37]), "+f"(d[38]), "+f"(d[39]),
        "+f"(d[40]), "+f"(d[41]), "+f"(d[42]), "+f"(d[43]), "+f"(d[44]), "+f"(d[45]), "+f"(d[46]), "+f"(d[47]),
        "+f"(d[48]), "+f"(d[49]), "+f"(d[50]), "+f"(d[51])
      : "l"(desc_a), "l"(desc_b), "n"(ACC));
}


__host__ __device__ constexpr bool via_mul(int b) { return b & 1; }
struct Dq {
  uint32_t addr[5], sh[5];
  uint32_t c[2];
  int tj;
};
__device__ __forceinline__ uint32_t neg_zero(uint16_t z) { return bf16x2_mul((uint32_t)z * 0x10001u, 0xBC80BC80u); }
__device__ __forceinline__ uint32_t out_scale(uint16_t s) { return bf16x2_mul((uint32_t)s * 0x10001u, 0x42804280u); }

template <int PITCH>
__device__ __forceinline__ void dq_setup(Dq& q, uint32_t base, int phase) {
  q.tj = (threadIdx.x & 3) - phase;
#pragma unroll
  for (int b = 0; b < 5; ++b) {
    const int e = 4 * b + q.tj + 5;
    const int o = (e * 52) >> 8;
    q.addr[b] = base + (o - 1) * PITCH;
    q.sh[b] = 6 * (e - 5 * o);
    if (via_mul(b)) asm("shr.u32 %0, 0x1000000, %1;" : "=r"(q.sh[b]) : "r"(q.sh[b]));
  }
}
template <int R0, int NR, int PITCH = kWPitch, int DST = R0>
__device__ __forceinline__ void dq_load(uint32_t (&a)[144], const Dq& q) {
#pragma unroll
  for (int i = R0; i < R0 + NR; ++i)
    asm volatile("ld.shared.u32 %0, [%1];"
                 : "=r"(a[i - R0 + DST])
                 : "r"(q.addr[(i >> 1) % 5] + ((i >> 1) / 5) * 4 * PITCH + (i & 1) * 32));
}
template <int R0, int NR, int DST = R0>
__device__ __forceinline__ void dq_math(uint32_t (&a)[144], const Dq& q) {
#pragma unroll
  for (int i = R0; i < R0 + NR; ++i) {
    const int u = i >> 1;
    uint32_t w = a[i - R0 + DST];
    if (via_mul(u % 5)) w = __byte_perm(w * q.sh[u % 5], 0, 0x3333);
    else w = __byte_perm(w >> q.sh[u % 5], 0, 0x0000);
    w = bf16x2_fma(w & 0x00380007u, 0x7D807F00u, q.c[i & 1]);
    if (u == 0) w = q.tj < 0 ? 0u : w;
    if (u == 71) w = q.tj > 0 ? 0u : w;
    a[i - R0 + DST] = w;
  }
}

template <int C>
__device__ __forceinline__ void mma_chunk(float (&d)[64], const uint32_t (&a)[144], uint64_t desc) {
  wgmma_fence();
#pragma unroll
  for (int s = 4 * C; s < 4 * C + 4; ++s) {
    if (s == 0) wgmma_rs_n128<0>(d, a[0], a[1], a[2], a[3], desc);
    else wgmma_rs_n128<1>(d, a[4 * s], a[4 * s + 1], a[4 * s + 2], a[4 * s + 3], desc + 2 * (s & 3));
  }
  wgmma_commit();
}
template <int C>
__device__ __forceinline__ void mma_chunk_extra(float (&d)[64], const uint32_t (&a)[144], uint64_t desc_a,
                                                uint64_t desc) {
  wgmma_fence();
#pragma unroll
  for (int kk = 0; kk < 4; ++kk) {
    if (C < kSS) {
      if (C == 0 && kk == 0) wgmma_ss_n104<0>(d, desc_a, desc);
      else wgmma_ss_n104<1>(d, desc_a + 128 * kk, desc + 2 * kk);
    } else {
      const int r = (16 * (C - kSS) + 4 * kk) % 144;
      wgmma_rs_n104<1>(d, a[r], a[r + 1], a[r + 2], a[r + 3], desc + 2 * kk);
    }
  }
  wgmma_commit();
}

struct Ctx {
  uint32_t sb;
  uint32_t empty_dst;
  uint64_t desc;
  int wg;
  bool extra;
  int phase_e;
  uint32_t zero;
  uint32_t sc[2];
  char* out_e;
  int rows_e;
};

template <int I>
__device__ __forceinline__ void boundary(const Ctx& cx) {
  asm volatile("{\n.reg .pred p;\nsetp.ne.s32 p, %0, %1;\n@p bra.uni OK;\ntrap;\nOK:\n}" ::"r"(cx.zero), "n"(I + 100)
               : "memory");
}

template <int G>
__device__ __forceinline__ void release(const Ctx& cx) {
  if (G + kStages >= 5 * kChunks) return;
  if ((G + kStages < 4 * kChunks || cx.extra) && (threadIdx.x & 31) < 2)
    asm volatile("mbarrier.arrive.shared::cluster.b64 _, [%0];" ::"r"(cx.empty_dst + ((G + kStages) % kStages) * 8)
                 : "memory");
}

__device__ __forceinline__ void wg_sync(int wg) {
  if (wg == 0) asm volatile("bar.sync 3, 128;" ::: "memory");
  else asm volatile("bar.sync 4, 128;" ::: "memory");
}

template <int MODE, int T, int C>
__device__ __forceinline__ void tile_step(float (&d)[64], uint32_t (&a)[144], Dq& q, Ctx& cx) {
  constexpr int G = T * kChunks + C, S = G % kStages;
  constexpr int lag = T == 0 ? kLagFirst : T == 3 ? kLagLast : kLagMid;
  const uint32_t sb = cx.sb;
  mbar_wait(sb + kBarFull + S * 8, (G / kStages) & 1);
  if (MODE != 3 && C == 0 && cx.wg == 1) asm volatile("bar.sync 1, 256;" ::: "memory");
  if (T == 3 && MODE == 0 && C == kGate && cx.wg == 1 && cx.extra) asm volatile("bar.sync 7, 256;" ::: "memory");
  if (MODE == 3) mma_chunk_extra<C>(d, a, cx.desc + (kOffAx + C * 8192) / 16, cx.desc + S * (kStageBytes / 16));
  else mma_chunk<C>(d, a, cx.desc + S * (kStageBytes / 16));
  if (MODE != 3 && lag == C && cx.wg == 0) asm volatile("bar.arrive 1, 256;" ::: "memory");
  if (MODE == 2 && C == 8) asm volatile("bar.arrive 7, 256;" ::: "memory");
  if (MODE == 1 && C < 8) {
    boundary<C>(cx);
    dq_math<head_end(C) % 144, head_end(C + 1) - head_end(C)>(a, q);
  }
  if (MODE == 2 && C == 0) {
    const int col = ((threadIdx.x >> 5) & 3) * 16 + ((threadIdx.x & 31) >> 2);
    dq_setup<kWePitch>(q, sb + kOffWe - kWeRow0 * kWePitch + col * 4, cx.phase_e);
    mbar_wait(sb + kBarWe, 0);
    q.c[0] = neg_zero(lds_u16(sb + kOffZS + col * 2));
    q.c[1] = neg_zero(lds_u16(sb + kOffZS + col * 2 + 16));
  }
  if (MODE == 3 && C == 1) {
    boundary<90>(cx);
    const int col = (threadIdx.x >> 5) * 16 + ((threadIdx.x & 31) >> 2);
    cx.sc[0] = out_scale(lds_u16(sb + kOffZS + 128 + col * 2));
    cx.sc[1] = out_scale(lds_u16(sb + kOffZS + 128 + col * 2 + 16));
  }
  if (MODE == 2 && C == 8) mbar_wait(sb + kBarAx, 0);
  if (MODE == 2 && C >= 2) {
    dq_load<16 * kSS + refill_end(C - 1), refill_end(C) - refill_end(C - 1), kWePitch, refill_end(C - 1)>(a, q);
    dq_math<16 * kSS + refill_end(C - 1), refill_end(C) - refill_end(C - 1), refill_end(C - 1)>(a, q);
  }
  if (C > 0 && MODE != 3) wgmma_wait<1>();
  if (MODE == 1 && C < 7) dq_load<head_end(C + 1) % 144, head_end(C + 2) - head_end(C + 1)>(a, q);
  if (C > 0 && MODE != 3) release<G - 1>(cx);
}

template <int MODE, int T>
__device__ __forceinline__ void tile(float (&d)[64], uint32_t (&a)[144], Dq& q, Ctx& cx) {
  constexpr int N = MODE == 3 ? kNX : 128;
  cx.sb += cx.zero;
  cx.desc += cx.zero;
  const uint32_t sb = cx.sb;
  tile_step<MODE, T, 0>(d, a, q, cx);
  tile_step<MODE, T, 1>(d, a, q, cx);
  tile_step<MODE, T, 2>(d, a, q, cx);
  tile_step<MODE, T, 3>(d, a, q, cx);
  tile_step<MODE, T, 4>(d, a, q, cx);
  tile_step<MODE, T, 5>(d, a, q, cx);
  tile_step<MODE, T, 6>(d, a, q, cx);
  tile_step<MODE, T, 7>(d, a, q, cx);
  tile_step<MODE, T, 8>(d, a, q, cx);
  const int lane = threadIdx.x & 31, warp = (threadIdx.x >> 5) & 3;
  if (MODE == 1 && lane == 0) mbar_arrive(sb + kBarDq);
  if (T > 0) mbar_wait(sb + kBarOutFree + cx.wg * 8, (T - 1) & 1);
  wgmma_wait<0>();
#pragma unroll
  for (int i = 0; i < N / 2; ++i) asm volatile("" : "+f"(d[i])::"memory");
  if (MODE != 3) release<T * kChunks + 8>(cx);
  const uint32_t st = sb + kOffOut + cx.wg * 16384 + ((lane & 7) + ((lane >> 4) << 3)) * 128 +
                      (((warp * 2 + ((lane >> 3) & 1)) ^ (lane & 7)) << 4);
  uint32_t r[32];
#pragma unroll
  for (int i = 0; i < N / 4; ++i)
    asm("cvt.rn.bf16x2.f32 %0, %1, %2;" : "=r"(r[i]) : "f"(d[2 * i + 1]), "f"(d[2 * i]));
  if (MODE != 3) boundary<200 + T>(cx);
#pragma unroll
  for (int i = 0; i < N / 8; i += 2) {
#pragma unroll
    for (int j = 0; j < 4; ++j)
      if (2 * i + j < N / 4) r[2 * i + j] = bf16x2_mul(r[2 * i + j], cx.sc[j & 1]);
    if (i + 1 < N / 8) {
      asm volatile("stmatrix.sync.aligned.m8n8.x4.trans.shared.b16 [%0], {%1, %2, %3, %4};" ::"r"(st + i * 1024),
                   "r"(r[2 * i]), "r"(r[2 * i + 1]), "r"(r[2 * i + 2]), "r"(r[2 * i + 3])
                   : "memory");
    } else {
      asm volatile("stmatrix.sync.aligned.m8n8.x2.trans.shared.b16 [%0], {%1, %2};" ::"r"(st + i * 1024), "r"(r[2 * i]),
                   "r"(r[2 * i + 1])
                   : "memory");
    }
  }
  if (MODE == 3) {
    asm volatile("bar.sync 3, 128;" ::: "memory");
    const int row = threadIdx.x >> 3, c = threadIdx.x & 7;
    const uint32_t src = sb + kOffOut + row * 128 + ((c ^ (row & 7)) << 4);
    char* dst = cx.out_e + (size_t)row * (8 * kF) + c * 16;
    uint4 v[7];
#pragma unroll
    for (int i = 0; i < 7; ++i)
      asm volatile("ld.shared.v4.u32 {%0, %1, %2, %3}, [%4];"
                   : "=r"(v[i].x), "=r"(v[i].y), "=r"(v[i].z), "=r"(v[i].w)
                   : "r"(src + i * 2048));
#pragma unroll
    for (int i = 0; i < 7; ++i)
      if (i < 6 || row < cx.rows_e - 96)
        asm volatile("st.global.v4.u32 [%0], {%1, %2, %3, %4};" ::"l"(dst + (size_t)i * 16 * 8 * kF), "r"(v[i].x),
                     "r"(v[i].y), "r"(v[i].z), "r"(v[i].w)
                     : "memory");
    return;
  }
  asm volatile("fence.proxy.async.shared::cta;" ::: "memory");
  __syncwarp();
  if (lane == 0) mbar_arrive(sb + kBarOutFull + cx.wg * 8);
}

__global__ void __cluster_dims__(2, 1, 1) __launch_bounds__(384, 1)
    gptq_gemm_kernel(const uint32_t* __restrict__ qw, const __nv_bfloat16* __restrict__ scales,
                     const __nv_bfloat16* __restrict__ zeros, __nv_bfloat16* __restrict__ out, const uint32_t zero,
                     const __grid_constant__ CUtensorMap tm_x64, const __grid_constant__ CUtensorMap tm_w,
                     const __grid_constant__ CUtensorMap tm_out, const __grid_constant__ CUtensorMap tm_x52,
                     const __grid_constant__ CUtensorMap tm_we) {
  extern __shared__ __align__(1024) uint8_t smem[];
  const uint32_t sb = (uint32_t)__cvta_generic_to_shared(smem);
  const int cid = blockIdx.x >> 1, rank = blockIdx.x & 1;
  const int phase = cid & 3, n_own = (cid >> 2) * 256 + rank * 128;
  uint16_t z0, z1, s0, s1;
  const int warp_id = __shfl_sync(0xffffffffu, (int)(threadIdx.x >> 5), 0);

  if (warp_id < 8) {
    asm volatile("barrier.cluster.arrive.relaxed.aligned;" ::: "memory");
    const uint32_t tid = threadIdx.x, r = (tid >> 4) & 7, c4 = (tid & 15) + ((tid >> 3) & 16);
    const uint32_t* src = qw + (r * kF + n_own + c4 * 4);
    const uint32_t dst = sb + kOffW + r * kWPitch + c4 * 16;
    cp_async16(dst, src);
    cp_async16(dst + 8 * kWPitch, src + 8 * kF);
    asm volatile("cp.async.commit_group;" ::: "memory");
    const uint32_t cz = n_own + (tid >> 5) * 16 + ((tid & 31) >> 2);
    const uint16_t* zp = reinterpret_cast<const uint16_t*>(zeros) + cz;
    const uint16_t* sp = reinterpret_cast<const uint16_t*>(scales) + cz;
    asm volatile("ld.global.nc.u16 %0, [%1];" : "=h"(z0) : "l"(zp));
    asm volatile("ld.global.nc.u16 %0, [%1+16];" : "=h"(z1) : "l"(zp));
    asm volatile("ld.global.nc.u16 %0, [%1];" : "=h"(s0) : "l"(sp));
    asm volatile("ld.global.nc.u16 %0, [%1+16];" : "=h"(s1) : "l"(sp));
    cp_async16(dst + 16 * kWPitch, src + 16 * kF);
    asm volatile("cp.async.commit_group;" ::: "memory");
  } else if (warp_id != 8) {
    asm volatile("barrier.cluster.arrive.relaxed.aligned;" ::: "memory");
    asm volatile("prefetch.tensormap [%0];" ::"l"(&tm_x64) : "memory");
  }
  const int wg = warp_id >> 2;
  const int lane = threadIdx.x & 31;

  const bool has_extra = cid < kExtraClusters;
  const int ue = kClusters + cid / 10;
  const int phase_e = ue & 3, n_e = (ue >> 2) * 256 + ((cid / 5) & 1) * 128 + rank * 64, row_e = (cid % 5) * kNX;

  if (wg == 2) {
    asm volatile("setmaxnreg.dec.sync.aligned.u32 24;");
    if (warp_id == 8) {
      uint32_t t0;
      {
        const bool leader = elect_one();
        if (leader) {
#pragma unroll
          for (int i = 0; i < kStages; ++i) mbar_init(sb + kBarFull + 8 * i, 1);
          asm volatile("fence.mbarrier_init.release.cluster;" ::: "memory");
        }
        __syncwarp();
        asm volatile("barrier.cluster.arrive.relaxed.aligned;" ::: "memory");
        asm volatile("barrier.cluster.wait.aligned;" ::: "memory");
        if (leader) {
          mbar_expect_tx(sb + kBarFull, kStageBytes);
          tma_load_2d_mc(sb + rank * 8192, &tm_x64, sb + kBarFull, phase * 568, rank * 64);
#pragma unroll
          for (int i = 0; i < kStages; ++i) mbar_init(sb + kBarEmpty + 8 * i, 16);
          mbar_init(sb + kBarWe, 1);
          mbar_init(sb + kBarDq, 8);
          mbar_init(sb + kBarAx, 2);
          mbar_init(sb + kBarLd, 1);
          mbar_init(sb + kBarOutFull, 4);
          mbar_init(sb + kBarOutFull + 8, 4);
          mbar_init(sb + kBarOutFree, 1);
          mbar_init(sb + kBarOutFree + 8, 1);
          asm volatile("fence.mbarrier_init.release.cluster;" ::: "memory");
        }
        asm volatile("mov.u32 %0, %clock;" : "=r"(t0));
        __syncwarp();
        asm volatile("bar.arrive 2, 288;" ::: "memory");
        asm volatile("bar.arrive 5, 128;" ::: "memory");
      }
      if (elect_one()) {
#pragma unroll
        for (int g = 1; g < kStages; ++g) {
          const uint32_t full = sb + kBarFull + g * 8;
          uint32_t t;
          do {
            asm volatile("mov.u32 %0, %clock;" : "=r"(t));
          } while (t - t0 < kPaceFirst + (g - 1) * kPace);
          uint32_t bytes = kStageBytes;
#pragma unroll
          for (int p = kFirst; p < 8; ++p)
            if (ride_step(p) == g) bytes += p < 7 ? 8 * kWPitch : 512;
          mbar_expect_tx(full, bytes);
          tma_load_2d_mc(sb + g * kStageBytes + rank * 8192, &tm_x64, full, phase * 568 + (g % kChunks) * 64,
                         rank * 64 + (g / kChunks) * 128);
#pragma unroll
          for (int p = kFirst; p < 8; ++p)
            if (ride_step(p) == g) {
              if (p < 7) tma_load_2d(sb + kOffW + p * 8 * kWPitch, &tm_w, full, n_own, p * 8);
              else bulk_load(sb + kOffW + 56 * kWPitch, qw + 56 * kF + n_own, 512, full);
            }
        }
        const int total = has_extra ? 5 * kChunks : 4 * kChunks;
        int c = kStages % kChunks, row = rank * 64 + (kStages / kChunks) * 128;
        uint32_t stage = 0, parity = 0;
#pragma unroll 1
        for (int g = kStages; g < total; ++g) {
          const uint32_t full = sb + kBarFull + stage * 8, dst = sb + stage * kStageBytes;
          mbar_wait_lazy(sb + kBarEmpty + stage * 8, parity);
          if (g < 4 * kChunks) {
            mbar_expect_tx(full, kStageBytes);
            tma_load_2d_mc(dst + rank * 8192, &tm_x64, full, phase * 568 + c * 64, row);
          } else {
            mbar_expect_tx(full, kNX * 128);
            tma_load_2d_mc(dst + rank * (kNX * 64), &tm_x52, full, phase_e * 568 + c * 64, row_e + rank * (kNX / 2));
          }
          if (++c == kChunks) { c = 0; row += 128; }
          if (++stage == kStages) { stage = 0; parity ^= 1; }
        }
        mbar_arrive(sb + kBarLd);
      }
    } else if (warp_id == 9) {
      asm volatile("prefetch.tensormap [%0];" ::"l"(&tm_w) : "memory");
      asm volatile("bar.sync 5, 128;" ::: "memory");
      if (elect_one()) {
#pragma unroll 1
        for (int i = 0; i < 8; ++i) {
          const int w = i & 1, t = i >> 1;
          if (i == 7) mbar_wait(sb + kBarOutFull + w * 8, t & 1);
          else mbar_wait_lazy(sb + kBarOutFull + w * 8, t & 1);
          if (i == 6) mbar_wait_lazy(sb + kBarLd, 0);
          tma_store_2d(&tm_out, sb + kOffOut + w * 16384, phase * kF + n_own + w * 64, t * 128);
          asm volatile("cp.async.bulk.commit_group;" ::: "memory");
          if (i < 7) {
            asm volatile("cp.async.bulk.wait_group.read 0;" ::: "memory");
            mbar_arrive(sb + kBarOutFree + w * 8);
          }
        }
        asm volatile("cp.async.bulk.wait_group.read 0;" ::: "memory");
      }
    } else {
      asm volatile("bar.sync 5, 128;" ::: "memory");
      if (has_extra) {
        const int h = threadIdx.x - 320, c4 = h & 15;
        const int colx = n_e + c4 * 4;
        mbar_wait_lazy(sb + kBarDq, 0);
        if (warp_id == 11 && elect_one()) {
          mbar_expect_tx(sb + kBarWe, kWeRows * kWePitch + 256);
          tma_load_2d(sb + kOffWe, &tm_we, sb + kBarWe, n_e, kWeRow0);
          bulk_load(sb + kOffZS, zeros + n_e, 128, sb + kBarWe);
          bulk_load(sb + kOffZS + 128, scales + n_e, 128, sb + kBarWe);
        }
        __syncwarp();
        uint32_t src = sb + kOffHead + (h >> 4) * 256 + c4 * 16;
#pragma unroll
        for (int i = 0; i < (kHeadRows + 3) / 4; ++i)
          if (4 * i + 3 < kHeadRows || 4 * i + (h >> 4) < kHeadRows)
            cp_async16(src + i * 1024, qw + ((h >> 4) + 4 * i) * kF + colx);
        const uint2 z2 = __ldg(reinterpret_cast<const uint2*>(zeros + colx));
        const uint32_t c[2] = {bf16x2_mul(z2.x, 0xBC80BC80u), bf16x2_mul(z2.y, 0xBC80BC80u)};
        if (h < 16 * phase_e)
          asm volatile("st.shared.v4.u32 [%0], {%1, %1, %1, %1};" ::"r"(sb + kOffAx + h * 16), "r"(0u) : "memory");
        uint32_t row = sb + kOffAx + (10 * (h >> 4) + 2 * phase_e) * 128 + c4 * 8;
        const uint32_t src_end = sb + kOffHead + kHeadRows * 256;
        asm volatile("cp.async.wait_all;" ::: "memory");
#pragma unroll 1
        for (; src < src_end; src += 1024, row += 40 * 128) {
          uint4 w;
          asm volatile("ld.shared.v4.u32 {%0, %1, %2, %3}, [%4];"
                       : "=r"(w.x), "=r"(w.y), "=r"(w.z), "=r"(w.w)
                       : "r"(src)
                       : "memory");
          uint32_t win[2], ad;
#pragma unroll
          for (int i = 0; i < 10; ++i) {
            constexpr uint32_t sel[4] = {0x5410, 0x6521, 0x7632, 0x7733};
            constexpr int pos[10] = {0, 3, 2, 1, 4, 3, 2, 5, 0, 3};
            if (i == 0 || i == 3 || i == 6 || i == 8) {
              const uint32_t se = sel[i == 0 ? 0 : i == 3 ? 1 : i == 6 ? 2 : 3];
              win[0] = __byte_perm(w.x, w.y, se);
              win[1] = __byte_perm(w.z, w.w, se);
            }
            uint32_t v[2];
#pragma unroll
            for (int j = 0; j < 2; ++j) {
              const uint32_t f = ((i == 2 || i == 5) ? win[j] >> 4 : win[j]) & (0x00070007u << pos[i]);
              v[j] = bf16x2_fma(f, 0x7F007F00u - pos[i] * 0x00800080u, c[j]);
            }
            if ((i & 1) == 0) {
              asm volatile("{\n.reg .u32 t;\nadd.u32 %0, %1, %2;\nshr.u32 t, %0, 3;\nlop3.b32 %0, %0, t, 0x70, 0x78;\n}"
                           : "=r"(ad)
                           : "r"(row), "r"(i * 128));
              asm volatile("st.shared.v2.u32 [%0], {%1, %2};" ::"r"(ad), "r"(v[0]), "r"(v[1]) : "memory");
            } else {
              asm volatile("st.shared.v2.u32 [%0+128], {%1, %2};" ::"r"(ad ^ 16), "r"(v[0]), "r"(v[1]) : "memory");
            }
          }
        }
        asm volatile("fence.proxy.async.shared::cta;" ::: "memory");
        __syncwarp();
        if (lane == 0) mbar_arrive(sb + kBarAx);
      }
    }
  } else {
    asm volatile("setmaxnreg.inc.sync.aligned.u32 240;");
    Ctx cx;
    cx.sb = sb;
    cx.wg = wg;
    cx.extra = has_extra;
    cx.phase_e = phase_e;
    cx.zero = zero;
    cx.desc = smem_desc(sb);
    asm("mapa.shared::cluster.u32 %0, %1, %2;" : "=r"(cx.empty_dst) : "r"(sb + kBarEmpty), "r"(lane & 1));
    float d[64];
    uint32_t a[144];
    Dq q;
    dq_setup<kWPitch>(q, sb + kOffW + (warp_id * 16 + (lane >> 2)) * 4, phase);
    q.c[0] = neg_zero(z0);
    q.c[1] = neg_zero(z1);
    cx.sc[0] = out_scale(s0);
    cx.sc[1] = out_scale(s1);
    asm volatile("cp.async.wait_group 1;" ::: "memory");
    wg_sync(wg);
    dq_load<0, kPre>(a, q);
    dq_math<0, kPre>(a, q);
    asm volatile("cp.async.wait_group 0;" ::: "memory");
    wg_sync(wg);
    dq_load<kPre, head_end(1) - kPre>(a, q);
    asm volatile("bar.sync 2, 288;" ::: "memory");
    tile<1, 0>(d, a, q, cx);
    tile<0, 1>(d, a, q, cx);
    tile<0, 2>(d, a, q, cx);
    if (wg == 0 && has_extra) {
      tile<2, 3>(d, a, q, cx);
      cx.out_e = reinterpret_cast<char*>(out) + ((size_t)(row_e * 4 + phase_e) * kF + n_e) * 2;
      cx.rows_e = min(kNX, kSup - row_e);
      tile<3, 4>(d, a, q, cx);
    } else {
      tile<0, 3>(d, a, q, cx);
    }
  }
}

typedef CUresult (*EncodeFn)(CUtensorMap*, CUtensorMapDataType, cuuint32_t, void*, const cuuint64_t*,
                             const cuuint64_t*, const cuuint32_t*, const cuuint32_t*, CUtensorMapInterleave,
                             CUtensorMapSwizzle, CUtensorMapL2promotion, CUtensorMapFloatOOBfill);

void make_map(EncodeFn enc, CUtensorMap* tm, CUtensorMapDataType dt, const void* base, uint64_t d0, uint64_t d1,
              uint64_t stride, uint32_t b0, uint32_t b1, CUtensorMapSwizzle sw, CUtensorMapL2promotion promo) {
  cuuint64_t dims[2] = {d0, d1};
  cuuint64_t strides[1] = {stride};
  cuuint32_t box[2] = {b0, b1};
  cuuint32_t es[2] = {1, 1};
  enc(tm, dt, 2, const_cast<void*>(base), dims, strides, box, es, CU_TENSOR_MAP_INTERLEAVE_NONE, sw, promo,
      CU_TENSOR_MAP_FLOAT_OOB_FILL_NONE);
}

}

extern "C" void kernel_launch(void* const* d_in, const int* in_sizes, int n_in, void* d_out, int out_size) {
  (void)in_sizes; (void)n_in; (void)out_size;
  static EncodeFn enc = nullptr;
  if (!enc) {
    void* fn = nullptr;
    cudaDriverEntryPointQueryResult qr;
    cudaGetDriverEntryPoint("cuTensorMapEncodeTiled", &fn, cudaEnableDefault, &qr);
    enc = (EncodeFn)fn;
    cudaFuncSetAttribute(gptq_gemm_kernel, cudaFuncAttributeMaxDynamicSharedMemorySize, kSmemBytes);
  }
  CUtensorMap x64, x52, w, we, o;
  make_map(enc, &x64, CU_TENSOR_MAP_DATA_TYPE_BFLOAT16, d_in[0], 2280, kSup, 4560, 64, 64, CU_TENSOR_MAP_SWIZZLE_128B,
           CU_TENSOR_MAP_L2_PROMOTION_L2_128B);
  make_map(enc, &x52, CU_TENSOR_MAP_DATA_TYPE_BFLOAT16, d_in[0], 2280, kSup, 4560, 64, kNX / 2,
           CU_TENSOR_MAP_SWIZZLE_128B, CU_TENSOR_MAP_L2_PROMOTION_L2_128B);
  make_map(enc, &w, CU_TENSOR_MAP_DATA_TYPE_INT32, d_in[1], kF, 57, kF * 4, 136, 8, CU_TENSOR_MAP_SWIZZLE_NONE,
           CU_TENSOR_MAP_L2_PROMOTION_L2_128B);
  make_map(enc, &we, CU_TENSOR_MAP_DATA_TYPE_INT32, d_in[1], kF, 57, kF * 4, 72, kWeRows, CU_TENSOR_MAP_SWIZZLE_NONE,
           CU_TENSOR_MAP_L2_PROMOTION_L2_128B);
  make_map(enc, &o, CU_TENSOR_MAP_DATA_TYPE_BFLOAT16, d_out, 4 * kF, kSup, 8 * kF, 64, 128, CU_TENSOR_MAP_SWIZZLE_128B,
           CU_TENSOR_MAP_L2_PROMOTION_NONE);
  gptq_gemm_kernel<<<2 * kClusters, 384, kSmemBytes>>>((const uint32_t*)d_in[1], (const __nv_bfloat16*)d_in[2],
                                                       (const __nv_bfloat16*)d_in[3], (__nv_bfloat16*)d_out, 0u, x64,
                                                       w, o, x52, we);
}
```

```cpp
#include <cuda.h>
#include <cuda_bf16.h>
#include <cuda_runtime.h>
#include <stdint.h>

namespace {

constexpr int kF = 4608;
constexpr int kSup = 512;
constexpr int kChunks = 9;
constexpr int kNX = 104;
constexpr int kClusters = 66;
constexpr int kExtraClusters = 60;

#define P_kPre 32
#define P_kLagFirst 0
#define P_kLagMid 4
#define P_kLagLast 4
#define P_kGate 5
#define P_kPaceFirst 500
#define P_kPace 400
#define P_kRefillFirst 3
#define PIN 0
#define LATE2 0
#define EARLYB 1
#define GATE0 6
#define GATE0A 8
#define HEND 8
#define GATE1 0
#define NOLAG 1
#define GATEA 8
#define HLATE 1
#define DEFER 4
#define EBND 1
constexpr int kPre = P_kPre;
constexpr int kLagFirst = P_kLagFirst;
constexpr int kLagMid = P_kLagMid;
constexpr int kLagLast = P_kLagLast;
constexpr int kGate = P_kGate;
constexpr int kPaceFirst = P_kPaceFirst;
constexpr int kPace = P_kPace;
constexpr int kSS = 2;
constexpr int kRefillFirst = P_kRefillFirst;

constexpr int kStages = 10;
constexpr int kStageBytes = 16384;
constexpr int kWPitch = 544;
constexpr int kWePitch = 288;
constexpr int kHeadRows = (64 * kSS + 9) / 10;
constexpr int kWeRow0 = (32 * kSS - 3) / 5;
constexpr int kWeRows = 57 - kWeRow0;
constexpr int kOffOut = kStages * kStageBytes;
constexpr int kOffW = kOffOut + 2 * 16384;
constexpr int kOffAx = kOffW;
constexpr int kOffWe = kOffAx + (10 * kHeadRows + 6) * 128;
constexpr int kOffHead = kOffWe + (kWeRows + 1) * kWePitch;
constexpr int kOffZS = kOffHead + kHeadRows * 256;
constexpr int kBarFull = kOffZS + 256;
constexpr int kBarEmpty = kBarFull + 8 * kStages;
constexpr int kBarWe = kBarEmpty + 8 * kStages;
constexpr int kBarDq = kBarWe + 8;
constexpr int kBarAx = kBarDq + 8;
constexpr int kBarLd = kBarAx + 8;
constexpr int kBarOutFull = kBarLd + 8;
constexpr int kBarOutFree = kBarOutFull + 16;
constexpr int kOffEnd = kBarOutFree + 16;
static_assert(kBarFull >= kOffW + 58 * kWPitch, "barriers must stay clear of the packed slab");

__host__ __device__ constexpr int head_end(int c) { return c >= HEND ? 144 : kPre + ((144 - kPre) * c + 2 * HEND - 1) / (2 * HEND) * 2; }
__host__ __device__ constexpr int last_word(int regs) { return (2 * regs - 1) / 5 > 56 ? 56 : (2 * regs - 1) / 5; }
constexpr int kFirst = last_word(head_end(2)) / 8 + 1;
__host__ __device__ constexpr int ride_step(int p) {
  int c = 0;
  while (c < 8 && last_word(head_end(c + 2)) < 8 * p) ++c;
  return c;
}
__host__ __device__ constexpr int refill_end(int c) {
  constexpr int total = 16 * (kChunks - kSS), steps = kChunks - kRefillFirst;
  return c < kRefillFirst ? 0 : c >= 8 ? total : ((total * (c - kRefillFirst + 1) + 2 * steps - 1) / (2 * steps)) * 2;
}
static_assert(kFirst <= 4 && last_word(kPre) < 16, "front groups");

constexpr int kSmemBytes = kOffEnd;
static_assert(kSmemBytes <= 232448, "smem");

__device__ __forceinline__ void mbar_init(uint32_t bar, uint32_t cnt) {
  asm volatile("mbarrier.init.shared::cta.b64 [%0], %1;" ::"r"(bar), "r"(cnt) : "memory");
}
__device__ __forceinline__ void mbar_expect_tx(uint32_t bar, uint32_t bytes) {
  asm volatile("mbarrier.arrive.expect_tx.shared::cta.b64 _, [%0], %1;" ::"r"(bar), "r"(bytes) : "memory");
}
__device__ __forceinline__ void mbar_arrive(uint32_t bar) {
  asm volatile("mbarrier.arrive.shared::cta.b64 _, [%0];" ::"r"(bar) : "memory");
}
__device__ __forceinline__ void mbar_wait(uint32_t bar, uint32_t parity) {
  asm volatile(
      "{\n.reg .pred p;\n.reg .u32 it;\n"
      "mbarrier.try_wait.parity.shared::cta.b64 p, [%0], %1;\n"
      "@p bra DONE;\n"
      "mov.u32 it, 0;\n"
      "SPIN:\n"
      "mbarrier.try_wait.parity.shared::cta.b64 p, [%0], %1;\n"
      "@p bra DONE;\n"
      "add.u32 it, it, 1;\n"
      "setp.lt.u32 p, it, 0x100000;\n"
      "@p bra SPIN;\n"
      "trap;\n"
      "DONE:\n}" ::"r"(bar),
      "r"(parity)
      : "memory");
}
__device__ __forceinline__ void mbar_wait_lazy(uint32_t bar, uint32_t parity) {
  asm volatile(
      "{\n.reg .pred p;\n.reg .u32 it;\n"
      "mov.u32 it, 0;\n"
      "SPIN:\n"
      "mbarrier.try_wait.parity.shared::cta.b64 p, [%0], %1, 4000;\n"
      "@p bra DONE;\n"
      "add.u32 it, it, 1;\n"
      "setp.lt.u32 p, it, 0x40000;\n"
      "@p bra SPIN;\n"
      "trap;\n"
      "DONE:\n}" ::"r"(bar),
      "r"(parity)
      : "memory");
}
__device__ __forceinline__ bool elect_one() {
  uint32_t p;
  asm volatile("{\n.reg .pred q;\nelect.sync _|q, 0xffffffff;\nselp.u32 %0, 1, 0, q;\n}" : "=r"(p));
  return p;
}
__device__ __forceinline__ void tma_load_2d(uint32_t dst, const CUtensorMap* tm, uint32_t bar, int c0, int c1) {
  asm volatile(
      "cp.async.bulk.tensor.2d.shared::cluster.global.mbarrier::complete_tx::bytes [%0], [%1, {%3, %4}], [%2];" ::"r"(dst),
      "l"(tm), "r"(bar), "r"(c0), "r"(c1)
      : "memory");
}
__device__ __forceinline__ void tma_load_2d_mc(uint32_t dst, const CUtensorMap* tm, uint32_t bar, int c0, int c1) {
  asm volatile(
      "cp.async.bulk.tensor.2d.shared::cluster.global.mbarrier::complete_tx::bytes.multicast::cluster [%0], [%1, {%3, "
      "%4}], [%2], %5;" ::"r"(dst),
      "l"(tm), "r"(bar), "r"(c0), "r"(c1), "h"((uint16_t)3)
      : "memory");
}
__device__ __forceinline__ void bulk_load(uint32_t dst, const void* src, uint32_t bytes, uint32_t bar) {
  asm volatile("cp.async.bulk.shared::cluster.global.mbarrier::complete_tx::bytes [%0], [%1], %2, [%3];" ::"r"(dst),
               "l"(src), "r"(bytes), "r"(bar)
               : "memory");
}
__device__ __forceinline__ void tma_store_2d(const CUtensorMap* tm, uint32_t src, int c0, int c1) {
  asm volatile("cp.async.bulk.tensor.2d.global.shared::cta.bulk_group [%0, {%2, %3}], [%1];" ::"l"(tm), "r"(src),
               "r"(c0), "r"(c1)
               : "memory");
}
__device__ __forceinline__ void cp_async16(uint32_t dst, const void* src) {
  asm volatile("cp.async.cg.shared.global [%0], [%1], 16;" ::"r"(dst), "l"(src) : "memory");
}
__device__ __forceinline__ uint16_t lds_u16(uint32_t addr) {
  uint16_t v;
  asm volatile("ld.shared.u16 %0, [%1];" : "=h"(v) : "r"(addr));
  return v;
}
__device__ __forceinline__ void wgmma_fence() { asm volatile("wgmma.fence.sync.aligned;" ::: "memory"); }
__device__ __forceinline__ void wgmma_commit() { asm volatile("wgmma.commit_group.sync.aligned;" ::: "memory"); }
template <int N>
__device__ __forceinline__ void wgmma_wait() {
  asm volatile("wgmma.wait_group.sync.aligned %0;" ::"n"(N) : "memory");
}
__device__ __forceinline__ uint64_t smem_desc(uint32_t addr) {
  return (uint64_t)((addr & 0x3FFFF) >> 4) | (1ull << 16) | (64ull << 32) | (1ull << 62);
}
__device__ __forceinline__ uint32_t bf16x2_fma(uint32_t a, uint32_t b, uint32_t c) {
  uint32_t d;
  asm("fma.rn.bf16x2 %0, %1, %2, %3;" : "=r"(d) : "r"(a), "r"(b), "r"(c));
  return d;
}
__device__ __forceinline__ uint32_t bf16x2_mul(uint32_t a, uint32_t b) {
  uint32_t d;
  asm("mul.rn.bf16x2 %0, %1, %2;" : "=r"(d) : "r"(a), "r"(b));
  return d;
}

template <int ACC>
__device__ __forceinline__ void wgmma_rs_n128(float (&d)[64], uint32_t a0, uint32_t a1, uint32_t a2, uint32_t a3,
                                              uint64_t desc_b) {
  asm volatile(
      "{\n.reg .pred p;\nsetp.ne.b32 p, %69, 0;\n"
      "wgmma.mma_async.sync.aligned.m64n128k16.f32.bf16.bf16 {"
      "%0, %1, %2, %3, %4, %5, %6, %7, %8, %9, %10, %11, %12, %13, %14, %15, "
      "%16, %17, %18, %19, %20, %21, %22, %23, %24, %25, %26, %27, %28, %29, %30, %31, "
      "%32, %33, %34, %35, %36, %37, %38, %39, %40, %41, %42, %43, %44, %45, %46, %47, "
      "%48, %49, %50, %51, %52, %53, %54, %55, %56, %57, %58, %59, %60, %61, %62, %63"
      "}, {%64, %65, %66, %67}, %68, p, 1, 1, 0;\n}\n"
      : "+f"(d[0]), "+f"(d[1]), "+f"(d[2]), "+f"(d[3]), "+f"(d[4]), "+f"(d[5]), "+f"(d[6]), "+f"(d[7]),
        "+f"(d[8]), "+f"(d[9]), "+f"(d[10]), "+f"(d[11]), "+f"(d[12]), "+f"(d[13]), "+f"(d[14]), "+f"(d[15]),
        "+f"(d[16]), "+f"(d[17]), "+f"(d[18]), "+f"(d[19]), "+f"(d[20]), "+f"(d[21]), "+f"(d[22]), "+f"(d[23]),
        "+f"(d[24]), "+f"(d[25]), "+f"(d[26]), "+f"(d[27]), "+f"(d[28]), "+f"(d[29]), "+f"(d[30]), "+f"(d[31]),
        "+f"(d[32]), "+f"(d[33]), "+f"(d[34]), "+f"(d[35]), "+f"(d[36]), "+f"(d[37]), "+f"(d[38]), "+f"(d[39]),
        "+f"(d[40]), "+f"(d[41]), "+f"(d[42]), "+f"(d[43]), "+f"(d[44]), "+f"(d[45]), "+f"(d[46]), "+f"(d[47]),
        "+f"(d[48]), "+f"(d[49]), "+f"(d[50]), "+f"(d[51]), "+f"(d[52]), "+f"(d[53]), "+f"(d[54]), "+f"(d[55]),
        "+f"(d[56]), "+f"(d[57]), "+f"(d[58]), "+f"(d[59]), "+f"(d[60]), "+f"(d[61]), "+f"(d[62]), "+f"(d[63])
      : "r"(a0), "r"(a1), "r"(a2), "r"(a3), "l"(desc_b), "n"(ACC));
}

template <int ACC>
__device__ __forceinline__ void wgmma_rs_n104(float (&d)[64], uint32_t a0, uint32_t a1, uint32_t a2, uint32_t a3,
                                              uint64_t desc_b) {
  asm volatile(
      "{\n.reg .pred p;\nsetp.ne.b32 p, %57, 0;\n"
      "wgmma.mma_async.sync.aligned.m64n104k16.f32.bf16.bf16 {"
      "%0, %1, %2, %3, %4, %5, %6, %7, %8, %9, %10, %11, %12, %13, %14, %15, "
      "%16, %17, %18, %19, %20, %21, %22, %23, %24, %25, %26, %27, %28, %29, %30, %31, "
      "%32, %33, %34, %35, %36, %37, %38, %39, %40, %41, %42, %43, %44, %45, %46, %47, "
      "%48, %49, %50, %51"
      "}, {%52, %53, %54, %55}, %56, p, 1, 1, 0;\n}\n"
      : "+f"(d[0]), "+f"(d[1]), "+f"(d[2]), "+f"(d[3]), "+f"(d[4]), "+f"(d[5]), "+f"(d[6]), "+f"(d[7]),
        "+f"(d[8]), "+f"(d[9]), "+f"(d[10]), "+f"(d[11]), "+f"(d[12]), "+f"(d[13]), "+f"(d[14]), "+f"(d[15]),
        "+f"(d[16]), "+f"(d[17]), "+f"(d[18]), "+f"(d[19]), "+f"(d[20]), "+f"(d[21]), "+f"(d[22]), "+f"(d[23]),
        "+f"(d[24]), "+f"(d[25]), "+f"(d[26]), "+f"(d[27]), "+f"(d[28]), "+f"(d[29]), "+f"(d[30]), "+f"(d[31]),
        "+f"(d[32]), "+f"(d[33]), "+f"(d[34]), "+f"(d[35]), "+f"(d[36]), "+f"(d[37]), "+f"(d[38]), "+f"(d[39]),
        "+f"(d[40]), "+f"(d[41]), "+f"(d[42]), "+f"(d[43]), "+f"(d[44]), "+f"(d[45]), "+f"(d[46]), "+f"(d[47]),
        "+f"(d[48]), "+f"(d[49]), "+f"(d[50]), "+f"(d[51])
      : "r"(a0), "r"(a1), "r"(a2), "r"(a3), "l"(desc_b), "n"(ACC));
}

template <int ACC>
__device__ __forceinline__ void wgmma_ss_n104(float (&d)[64], uint64_t desc_a, uint64_t desc_b) {
  asm volatile(
      "{\n.reg .pred p;\nsetp.ne.b32 p, %54, 0;\n"
      "wgmma.mma_async.sync.aligned.m64n104k16.f32.bf16.bf16 {"
      "%0, %1, %2, %3, %4, %5, %6, %7, %8, %9, %10, %11, %12, %13, %14, %15, "
      "%16, %17, %18, %19, %20, %21, %22, %23, %24, %25, %26, %27, %28, %29, %30, %31, "
      "%32, %33, %34, %35, %36, %37, %38, %39, %40, %41, %42, %43, %44, %45, %46, %47, "
      "%48, %49, %50, %51"
      "}, %52, %53, p, 1, 1, 1, 0;\n}\n"
      : "+f"(d[0]), "+f"(d[1]), "+f"(d[2]), "+f"(d[3]), "+f"(d[4]), "+f"(d[5]), "+f"(d[6]), "+f"(d[7]),
        "+f"(d[8]), "+f"(d[9]), "+f"(d[10]), "+f"(d[11]), "+f"(d[12]), "+f"(d[13]), "+f"(d[14]), "+f"(d[15]),
        "+f"(d[16]), "+f"(d[17]), "+f"(d[18]), "+f"(d[19]), "+f"(d[20]), "+f"(d[21]), "+f"(d[22]), "+f"(d[23]),
        "+f"(d[24]), "+f"(d[25]), "+f"(d[26]), "+f"(d[27]), "+f"(d[28]), "+f"(d[29]), "+f"(d[30]), "+f"(d[31]),
        "+f"(d[32]), "+f"(d[33]), "+f"(d[34]), "+f"(d[35]), "+f"(d[36]), "+f"(d[37]), "+f"(d[38]), "+f"(d[39]),
        "+f"(d[40]), "+f"(d[41]), "+f"(d[42]), "+f"(d[43]), "+f"(d[44]), "+f"(d[45]), "+f"(d[46]), "+f"(d[47]),
        "+f"(d[48]), "+f"(d[49]), "+f"(d[50]), "+f"(d[51])
      : "l"(desc_a), "l"(desc_b), "n"(ACC));
}

__host__ __device__ constexpr bool via_mul(int b) { return b & 1; }
struct Dq {
  uint32_t addr[5], sh[5];
  uint32_t c[2];
  int tj;
};
__device__ __forceinline__ uint32_t neg_zero(uint16_t z) { return bf16x2_mul((uint32_t)z * 0x10001u, 0xBC80BC80u); }
__device__ __forceinline__ uint32_t out_scale(uint16_t s) { return bf16x2_mul((uint32_t)s * 0x10001u, 0x42804280u); }

template <int PITCH>
__device__ __forceinline__ void dq_setup(Dq& q, uint32_t base, int phase) {
  q.tj = (threadIdx.x & 3) - phase;
#pragma unroll
  for (int b = 0; b < 5; ++b) {
    const int e = 4 * b + q.tj + 5;
    const int o = (e * 52) >> 8;
    q.addr[b] = base + (o - 1) * PITCH;
    q.sh[b] = 6 * (e - 5 * o);
    if (via_mul(b)) asm("shr.u32 %0, 0x1000000, %1;" : "=r"(q.sh[b]) : "r"(q.sh[b]));
  }
}
template <int R0, int NR, int PITCH = kWPitch, int DST = R0>
__device__ __forceinline__ void dq_load(uint32_t (&a)[144], const Dq& q) {
#pragma unroll
  for (int i = R0; i < R0 + NR; ++i)
    asm volatile("ld.shared.u32 %0, [%1];"
                 : "=r"(a[i - R0 + DST])
                 : "r"(q.addr[(i >> 1) % 5] + ((i >> 1) / 5) * 4 * PITCH + (i & 1) * 32));
}
template <int R0, int NR, int DST = R0>
__device__ __forceinline__ void dq_math(uint32_t (&a)[144], const Dq& q) {
#pragma unroll
  for (int i = R0; i < R0 + NR; ++i) {
    const int u = i >> 1;
    uint32_t w = a[i - R0 + DST];
    if (via_mul(u % 5)) w = __byte_perm(w * q.sh[u % 5], 0, 0x3333);
    else w = __byte_perm(w >> q.sh[u % 5], 0, 0x0000);
    w = bf16x2_fma(w & 0x00380007u, 0x7D807F00u, q.c[i & 1]);
    if (u == 0) w = q.tj < 0 ? 0u : w;
    if (u == 71) w = q.tj > 0 ? 0u : w;
    a[i - R0 + DST] = w;
  }
}

template <int C>
__device__ __forceinline__ void mma_chunk(float (&d)[64], const uint32_t (&a)[144], uint64_t desc) {
  wgmma_fence();
#pragma unroll
  for (int s = 4 * C; s < 4 * C + 4; ++s) {
    if (s == 0) wgmma_rs_n128<0>(d, a[0], a[1], a[2], a[3], desc);
    else wgmma_rs_n128<1>(d, a[4 * s], a[4 * s + 1], a[4 * s + 2], a[4 * s + 3], desc + 2 * (s & 3));
  }
  wgmma_commit();
}
template <int C>
__device__ __forceinline__ void mma_chunk_extra(float (&d)[64], const uint32_t (&a)[144], uint64_t desc_a,
                                                uint64_t desc) {
  wgmma_fence();
#pragma unroll
  for (int kk = 0; kk < 4; ++kk) {
    if (C < kSS) {
      if (C == 0 && kk == 0) wgmma_ss_n104<0>(d, desc_a, desc);
      else wgmma_ss_n104<1>(d, desc_a + 128 * kk, desc + 2 * kk);
    } else {
      const int r = (16 * (C - kSS) + 4 * kk) % 144;
      wgmma_rs_n104<1>(d, a[r], a[r + 1], a[r + 2], a[r + 3], desc + 2 * kk);
    }
  }
  wgmma_commit();
}

struct Ctx {
  uint32_t sb;
  uint32_t empty_dst;
  uint64_t desc;
  int wg;
  bool extra;
  int phase_e;
  uint32_t zero;
  uint32_t sc[2];
  char* out_e;
  int rows_e;
};

template <int I>
__device__ __forceinline__ void boundary(const Ctx& cx) {
  asm volatile("{\n.reg .pred p;\nsetp.ne.s32 p, %0, %1;\n@p bra.uni OK;\ntrap;\nOK:\n}" ::"r"(cx.zero), "n"(I + 100)
               : "memory");
}

template <int G>
__device__ __forceinline__ void release(const Ctx& cx) {
  if (G + kStages >= 5 * kChunks) return;
  if ((G + kStages < 4 * kChunks || cx.extra) && (threadIdx.x & 31) < 2)
    asm volatile("mbarrier.arrive.shared::cluster.b64 _, [%0];" ::"r"(cx.empty_dst + ((G + kStages) % kStages) * 8)
                 : "memory");
}

__device__ __forceinline__ void wg_sync(int wg) {
  if (wg == 0) asm volatile("bar.sync 3, 128;" ::: "memory");
  else asm volatile("bar.sync 4, 128;" ::: "memory");
}

template <int I0, int I1, int N>
__device__ __forceinline__ void stage_rows(uint32_t (&r)[32], const Ctx& cx) {
  const int lane = threadIdx.x & 31, warp = (threadIdx.x >> 5) & 3;
  const uint32_t st = cx.sb + kOffOut + cx.wg * 16384 + ((lane & 7) + ((lane >> 4) << 3)) * 128 +
                      (((warp * 2 + ((lane >> 3) & 1)) ^ (lane & 7)) << 4);
#pragma unroll
  for (int i = I0; i < I1; ++i) {
#pragma unroll
    for (int j = 0; j < 4; ++j)
      if (4 * i + j < N / 4) r[4 * i + j] = bf16x2_mul(r[4 * i + j], cx.sc[j & 1]);
    if (4 * i + 2 < N / 4) {
      asm volatile("stmatrix.sync.aligned.m8n8.x4.trans.shared.b16 [%0], {%1, %2, %3, %4};" ::"r"(st + i * 2048),
                   "r"(r[4 * i]), "r"(r[4 * i + 1]), "r"(r[4 * i + 2]), "r"(r[4 * i + 3])
                   : "memory");
    } else {
      asm volatile("stmatrix.sync.aligned.m8n8.x2.trans.shared.b16 [%0], {%1, %2};" ::"r"(st + i * 2048), "r"(r[4 * i]),
                   "r"(r[4 * i + 1])
                   : "memory");
    }
  }
}
__device__ __forceinline__ void hand_over(const Ctx& cx) {
  asm volatile("fence.proxy.async.shared::cta;" ::: "memory");
  __syncwarp();
  if ((threadIdx.x & 31) == 0) mbar_arrive(cx.sb + kBarOutFull + cx.wg * 8);
}

template <int MODE, int T, int C>
__device__ __forceinline__ void tile_step(float (&d)[64], uint32_t (&a)[144], uint32_t (&r)[32], Dq& q, Ctx& cx) {
  constexpr int G = T * kChunks + C, S = G % kStages;
  constexpr int lag = T == 0 ? kLagFirst : T == 3 ? kLagLast : kLagMid;
  const uint32_t sb = cx.sb;
  mbar_wait(sb + kBarFull + S * 8, (G / kStages) & 1);
  if (MODE != 3 && !((NOLAG >> T) & 1) && C == 0 && cx.wg == 1) asm volatile("bar.sync 1, 256;" ::: "memory");
  if (T == 3 && MODE == 0 && C == kGate && cx.wg == 1 && cx.extra) asm volatile("bar.sync 7, 256;" ::: "memory");
  if (((GATE0 && T == 0 && C == GATE0) || (GATE1 && (T == 1 || T == 2) && C == GATE1)) && cx.wg == 1) asm volatile("bar.sync 6, 256;" ::: "memory");
  if (MODE == 3) mma_chunk_extra<C>(d, a, cx.desc + (kOffAx + C * 8192) / 16, cx.desc + S * (kStageBytes / 16));
  else mma_chunk<C>(d, a, cx.desc + S * (kStageBytes / 16));
  if (MODE != 3 && !((NOLAG >> T) & 1) && lag == C && cx.wg == 0) asm volatile("bar.arrive 1, 256;" ::: "memory");
  if (MODE == 2 && C == GATEA) asm volatile("bar.arrive 7, 256;" ::: "memory");
  if (((GATE0 && T == 0 && C == GATE0A) || (GATE1 && (T == 1 || T == 2) && C == 8)) && cx.wg == 0) asm volatile("bar.arrive 6, 256;" ::: "memory");
  if (DEFER && T > 0 && C == 0) {
    boundary<300 + T + 10 * MODE>(cx);
    stage_rows<8 - DEFER, 8, 128>(r, cx);
    hand_over(cx);
  }
  if (MODE == 1 && C < 8) {
    boundary<C>(cx);
    if (LATE2 && C == 0) {
      asm volatile("cp.async.wait_group 0;" ::: "memory");
      wg_sync(cx.wg);
      dq_load<kPre, head_end(1) - kPre>(a, q);
    }
    dq_math<head_end(C) % 144, head_end(C + 1) - head_end(C)>(a, q);
  }
  if (MODE == 2 && C == 0) {
    const int col = ((threadIdx.x >> 5) & 3) * 16 + ((threadIdx.x & 31) >> 2);
    dq_setup<kWePitch>(q, sb + kOffWe - kWeRow0 * kWePitch + col * 4, cx.phase_e);
    mbar_wait(sb + kBarWe, 0);
    q.c[0] = neg_zero(lds_u16(sb + kOffZS + col * 2));
    q.c[1] = neg_zero(lds_u16(sb + kOffZS + col * 2 + 16));
  }
  if (MODE == 3 && C == 1) {
    boundary<90>(cx);
    const int col = (threadIdx.x >> 5) * 16 + ((threadIdx.x & 31) >> 2);
    cx.sc[0] = out_scale(lds_u16(sb + kOffZS + 128 + col * 2));
    cx.sc[1] = out_scale(lds_u16(sb + kOffZS + 128 + col * 2 + 16));
  }
  if (MODE == 2 && C == 8) mbar_wait(sb + kBarAx, 0);
  if (MODE == 2 && C >= 2) {
    dq_load<16 * kSS + refill_end(C - 1), refill_end(C) - refill_end(C - 1), kWePitch, refill_end(C - 1)>(a, q);
    dq_math<16 * kSS + refill_end(C - 1), refill_end(C) - refill_end(C - 1), refill_end(C - 1)>(a, q);
  }
  if (C > 0 && MODE != 3) wgmma_wait<1>();
  if (MODE == 1 && C < 7) dq_load<head_end(C + 1) % 144, head_end(C + 2) - head_end(C + 1)>(a, q);
  if (C > 0 && MODE != 3) release<G - 1>(cx);
}

template <int MODE, int T>
__device__ __forceinline__ void tile(float (&d)[64], uint32_t (&a)[144], uint32_t (&r)[32], Dq& q, Ctx& cx) {
  constexpr int N = MODE == 3 ? kNX : 128;
  cx.sb += cx.zero;
  cx.desc += cx.zero;
  const uint32_t sb = cx.sb;
  tile_step<MODE, T, 0>(d, a, r, q, cx);
  tile_step<MODE, T, 1>(d, a, r, q, cx);
  tile_step<MODE, T, 2>(d, a, r, q, cx);
  tile_step<MODE, T, 3>(d, a, r, q, cx);
  tile_step<MODE, T, 4>(d, a, r, q, cx);
  tile_step<MODE, T, 5>(d, a, r, q, cx);
  tile_step<MODE, T, 6>(d, a, r, q, cx);
  tile_step<MODE, T, 7>(d, a, r, q, cx);
  tile_step<MODE, T, 8>(d, a, r, q, cx);
  const int lane = threadIdx.x & 31;
  if (!HLATE && MODE == 1 && lane == 0) mbar_arrive(sb + kBarDq);
  if (T > 0) mbar_wait(sb + kBarOutFree + cx.wg * 8, (T - 1) & 1);
  wgmma_wait<0>();
#pragma unroll
  for (int i = 0; i < N / 2; ++i) asm volatile("" : "+f"(d[i])::"memory");
  if (MODE != 3) release<T * kChunks + 8>(cx);
#pragma unroll
  for (int i = 0; i < N / 4; ++i)
    asm("cvt.rn.bf16x2.f32 %0, %1, %2;" : "=r"(r[i]) : "f"(d[2 * i + 1]), "f"(d[2 * i]));
  if (EBND && MODE != 3) boundary<200 + T + 10 * MODE>(cx);
  constexpr bool last = MODE == 3 || (MODE == 0 && T == 3);
  stage_rows<0, last ? (N + 15) / 16 : 8 - DEFER, N>(r, cx);
  if (DEFER && !last) return;
  if (MODE == 3) {
    asm volatile("bar.sync 3, 128;" ::: "memory");
    const int row = threadIdx.x >> 3, c = threadIdx.x & 7;
    const uint32_t src = sb + kOffOut + row * 128 + ((c ^ (row & 7)) << 4);
    char* dst = cx.out_e + (size_t)row * (8 * kF) + c * 16;
    uint4 v[7];
#pragma unroll
    for (int i = 0; i < 7; ++i)
      asm volatile("ld.shared.v4.u32 {%0, %1, %2, %3}, [%4];"
                   : "=r"(v[i].x), "=r"(v[i].y), "=r"(v[i].z), "=r"(v[i].w)
                   : "r"(src + i * 2048));
#pragma unroll
    for (int i = 0; i < 7; ++i)
      if (i < 6 || row < cx.rows_e - 96)
        asm volatile("st.global.v4.u32 [%0], {%1, %2, %3, %4};" ::"l"(dst + (size_t)i * 16 * 8 * kF), "r"(v[i].x),
                     "r"(v[i].y), "r"(v[i].z), "r"(v[i].w)
                     : "memory");
    return;
  }
  hand_over(cx);
}

__global__ void __cluster_dims__(2, 1, 1) __launch_bounds__(384, 1)
    gptq_gemm_kernel(const uint32_t* __restrict__ qw, const __nv_bfloat16* __restrict__ scales,
                     const __nv_bfloat16* __restrict__ zeros, __nv_bfloat16* __restrict__ out, const uint32_t zero,
                     const __grid_constant__ CUtensorMap tm_x64, const __grid_constant__ CUtensorMap tm_w,
                     const __grid_constant__ CUtensorMap tm_out, const __grid_constant__ CUtensorMap tm_x52,
                     const __grid_constant__ CUtensorMap tm_we) {
  extern __shared__ __align__(1024) uint8_t smem[];
  const uint32_t sb = (uint32_t)__cvta_generic_to_shared(smem);
  const int cid = blockIdx.x >> 1, rank = blockIdx.x & 1;
  const int phase = cid & 3, n_own = (cid >> 2) * 256 + rank * 128;
  uint16_t z0, z1, s0, s1;
  const int warp_id = __shfl_sync(0xffffffffu, (int)(threadIdx.x >> 5), 0);

  if (warp_id < 8) {
    asm volatile("barrier.cluster.arrive.relaxed.aligned;" ::: "memory");
    const uint32_t tid = threadIdx.x, r = (tid >> 4) & 7, c4 = (tid & 15) + ((tid >> 3) & 16);
    const uint32_t* src = qw + (r * kF + n_own + c4 * 4);
    const uint32_t dst = sb + kOffW + r * kWPitch + c4 * 16;
    cp_async16(dst, src);
    cp_async16(dst + 8 * kWPitch, src + 8 * kF);
    asm volatile("cp.async.commit_group;" ::: "memory");
    const uint32_t cz = n_own + (tid >> 5) * 16 + ((tid & 31) >> 2);
    const uint16_t* zp = reinterpret_cast<const uint16_t*>(zeros) + cz;
    const uint16_t* sp = reinterpret_cast<const uint16_t*>(scales) + cz;
    asm volatile("ld.global.nc.u16 %0, [%1];" : "=h"(z0) : "l"(zp));
    asm volatile("ld.global.nc.u16 %0, [%1+16];" : "=h"(z1) : "l"(zp));
    asm volatile("ld.global.nc.u16 %0, [%1];" : "=h"(s0) : "l"(sp));
    asm volatile("ld.global.nc.u16 %0, [%1+16];" : "=h"(s1) : "l"(sp));
    cp_async16(dst + 16 * kWPitch, src + 16 * kF);
    if (kFirst > 3) cp_async16(dst + 24 * kWPitch, src + 24 * kF);
    asm volatile("cp.async.commit_group;" ::: "memory");
  } else if (warp_id != 8) {
    asm volatile("barrier.cluster.arrive.relaxed.aligned;" ::: "memory");
    asm volatile("prefetch.tensormap [%0];" ::"l"(&tm_x64) : "memory");
  }
  const int wg = warp_id >> 2;
  const int lane = threadIdx.x & 31;

  const bool has_extra = cid < kExtraClusters;
  const int ue = kClusters + cid / 10;
  const int phase_e = ue & 3, n_e = (ue >> 2) * 256 + ((cid / 5) & 1) * 128 + rank * 64, row_e = (cid % 5) * kNX;

  if (wg == 2) {
    asm volatile("setmaxnreg.dec.sync.aligned.u32 24;");
    if (warp_id >= 10) {
      asm volatile("bar.sync 5, 128;" ::: "memory");
      if (has_extra) {
        const int h = threadIdx.x - 320, c4 = h & 15;
        const int colx = n_e + c4 * 4;
        mbar_wait_lazy(sb + (HLATE ? kBarOutFull + 8 : kBarDq), 0);
        if (warp_id == 11 && elect_one()) {
          mbar_expect_tx(sb + kBarWe, kWeRows * kWePitch + 256);
          tma_load_2d(sb + kOffWe, &tm_we, sb + kBarWe, n_e, kWeRow0);
          bulk_load(sb + kOffZS, zeros + n_e, 128, sb + kBarWe);
          bulk_load(sb + kOffZS + 128, scales + n_e, 128, sb + kBarWe);
        }
        __syncwarp();
        uint32_t src = sb + kOffHead + (h >> 4) * 256 + c4 * 16;
#pragma unroll
        for (int i = 0; i < (kHeadRows + 3) / 4; ++i)
          if (4 * i + 3 < kHeadRows || 4 * i + (h >> 4) < kHeadRows)
            cp_async16(src + i * 1024, qw + ((h >> 4) + 4 * i) * kF + colx);
        const uint2 z2 = __ldg(reinterpret_cast<const uint2*>(zeros + colx));
        const uint32_t c[2] = {bf16x2_mul(z2.x, 0xBC80BC80u), bf16x2_mul(z2.y, 0xBC80BC80u)};
        if (h < 16 * phase_e)
          asm volatile("st.shared.v4.u32 [%0], {%1, %1, %1, %1};" ::"r"(sb + kOffAx + h * 16), "r"(0u) : "memory");
        uint32_t row = sb + kOffAx + (10 * (h >> 4) + 2 * phase_e) * 128 + c4 * 8;
        const uint32_t src_end = sb + kOffHead + kHeadRows * 256;
        asm volatile("cp.async.wait_all;" ::: "memory");
#pragma unroll 1
        for (; src < src_end; src += 1024, row += 40 * 128) {
          uint4 w;
          asm volatile("ld.shared.v4.u32 {%0, %1, %2, %3}, [%4];"
                       : "=r"(w.x), "=r"(w.y), "=r"(w.z), "=r"(w.w)
                       : "r"(src)
                       : "memory");
          uint32_t win[2], ad;
#pragma unroll
          for (int i = 0; i < 10; ++i) {
            constexpr uint32_t sel[4] = {0x5410, 0x6521, 0x7632, 0x7733};
            constexpr int pos[10] = {0, 3, 2, 1, 4, 3, 2, 5, 0, 3};
            if (i == 0 || i == 3 || i == 6 || i == 8) {
              const uint32_t se = sel[i == 0 ? 0 : i == 3 ? 1 : i == 6 ? 2 : 3];
              win[0] = __byte_perm(w.x, w.y, se);
              win[1] = __byte_perm(w.z, w.w, se);
            }
            uint32_t v[2];
#pragma unroll
            for (int j = 0; j < 2; ++j) {
              const uint32_t f = ((i == 2 || i == 5) ? win[j] >> 4 : win[j]) & (0x00070007u << pos[i]);
              v[j] = bf16x2_fma(f, 0x7F007F00u - pos[i] * 0x00800080u, c[j]);
            }
            if ((i & 1) == 0) {
              asm volatile("{\n.reg .u32 t;\nadd.u32 %0, %1, %2;\nshr.u32 t, %0, 3;\nlop3.b32 %0, %0, t, 0x70, 0x78;\n}"
                           : "=r"(ad)
                           : "r"(row), "r"(i * 128));
              asm volatile("st.shared.v2.u32 [%0], {%1, %2};" ::"r"(ad), "r"(v[0]), "r"(v[1]) : "memory");
            } else {
              asm volatile("st.shared.v2.u32 [%0+128], {%1, %2};" ::"r"(ad ^ 16), "r"(v[0]), "r"(v[1]) : "memory");
            }
          }
        }
        asm volatile("fence.proxy.async.shared::cta;" ::: "memory");
        __syncwarp();
        if (lane == 0) mbar_arrive(sb + kBarAx);
      }
    } else if (warp_id == 9) {
      if (elect_one()) {
#pragma unroll
          for (int i = 0; i < kStages; ++i) mbar_init(sb + kBarEmpty + 8 * i, 16);
          mbar_init(sb + kBarWe, 1);
          mbar_init(sb + kBarDq, 8);
          mbar_init(sb + kBarAx, 2);
          mbar_init(sb + kBarLd, 1);
          mbar_init(sb + kBarOutFull, 4);
          mbar_init(sb + kBarOutFull + 8, 4);
          mbar_init(sb + kBarOutFree, 1);
          mbar_init(sb + kBarOutFree + 8, 1);
          asm volatile("fence.mbarrier_init.release.cluster;" ::: "memory");
        asm volatile("prefetch.tensormap [%0];" ::"l"(&tm_w) : "memory");
      }
      __syncwarp();
      asm volatile("bar.arrive 2, 320;" ::: "memory");
      asm volatile("bar.sync 5, 128;" ::: "memory");
      if (elect_one()) {
#pragma unroll 1
        for (int i = 0; i < 8; ++i) {
          const int w = i & 1, t = i >> 1;
          if (i == 7) mbar_wait(sb + kBarOutFull + w * 8, t & 1);
          else mbar_wait_lazy(sb + kBarOutFull + w * 8, t & 1);
          if (i == 6) mbar_wait_lazy(sb + kBarLd, 0);
          tma_store_2d(&tm_out, sb + kOffOut + w * 16384, phase * kF + n_own + w * 64, t * 128);
          asm volatile("cp.async.bulk.commit_group;" ::: "memory");
          if (i < 7) {
            asm volatile("cp.async.bulk.wait_group.read 0;" ::: "memory");
            mbar_arrive(sb + kBarOutFree + w * 8);
          }
        }
        asm volatile("cp.async.bulk.wait_group.read 0;" ::: "memory");
      }
    } else {
      uint32_t t0;
      {
        const bool leader = elect_one();
        if (leader) {
#pragma unroll
          for (int i = 0; i < kStages; ++i) mbar_init(sb + kBarFull + 8 * i, 1);
          asm volatile("fence.mbarrier_init.release.cluster;" ::: "memory");
        }
        __syncwarp();
        asm volatile("barrier.cluster.arrive.relaxed.aligned;" ::: "memory");
        asm volatile("barrier.cluster.wait.aligned;" ::: "memory");
        if (leader) {
          mbar_expect_tx(sb + kBarFull, kStageBytes);
          tma_load_2d_mc(sb + rank * 8192, &tm_x64, sb + kBarFull, phase * 568, rank * 64);
        }
        asm volatile("mov.u32 %0, %clock;" : "=r"(t0));
        __syncwarp();
        asm volatile("bar.arrive 2, 320;" ::: "memory");
        asm volatile("bar.sync 5, 128;" ::: "memory");
      }
      if (elect_one()) {
#pragma unroll
        for (int g = 1; g < kStages; ++g) {
          const uint32_t full = sb + kBarFull + g * 8;
          uint32_t t;
          do {
            asm volatile("mov.u32 %0, %clock;" : "=r"(t));
          } while (t - t0 < kPaceFirst + (g - 1) * kPace);
          uint32_t bytes = kStageBytes;
#pragma unroll
          for (int p = kFirst; p < 8; ++p)
            if (ride_step(p) == g) bytes += p < 7 ? 8 * kWPitch : 512;
          mbar_expect_tx(full, bytes);
          tma_load_2d_mc(sb + g * kStageBytes + rank * 8192, &tm_x64, full, phase * 568 + (g % kChunks) * 64,
                         rank * 64 + (g / kChunks) * 128);
#pragma unroll
          for (int p = kFirst; p < 8; ++p)
            if (ride_step(p) == g) {
              if (p < 7) tma_load_2d(sb + kOffW + p * 8 * kWPitch, &tm_w, full, n_own, p * 8);
              else bulk_load(sb + kOffW + 56 * kWPitch, qw + 56 * kF + n_own, 512, full);
            }
        }
        const int total = has_extra ? 5 * kChunks : 4 * kChunks;
        int c = kStages % kChunks, row = rank * 64 + (kStages / kChunks) * 128;
        uint32_t stage = 0, parity = 0;
#pragma unroll 1
        for (int g = kStages; g < total; ++g) {
          const uint32_t full = sb + kBarFull + stage * 8, dst = sb + stage * kStageBytes;
          mbar_wait_lazy(sb + kBarEmpty + stage * 8, parity);
          if (g < 4 * kChunks) {
            mbar_expect_tx(full, kStageBytes);
            tma_load_2d_mc(dst + rank * 8192, &tm_x64, full, phase * 568 + c * 64, row);
          } else {
            mbar_expect_tx(full, kNX * 128);
            tma_load_2d_mc(dst + rank * (kNX * 64), &tm_x52, full, phase_e * 568 + c * 64, row_e + rank * (kNX / 2));
          }
          if (++c == kChunks) { c = 0; row += 128; }
          if (++stage == kStages) { stage = 0; parity ^= 1; }
        }
        mbar_arrive(sb + kBarLd);
      }
    }
  } else {
    asm volatile("setmaxnreg.inc.sync.aligned.u32 240;");
    Ctx cx;
    cx.sb = sb;
    cx.wg = wg;
    cx.extra = has_extra;
    cx.phase_e = phase_e;
    cx.zero = zero;
    cx.desc = smem_desc(sb);
    asm("mapa.shared::cluster.u32 %0, %1, %2;" : "=r"(cx.empty_dst) : "r"(sb + kBarEmpty), "r"(lane & 1));
    float d[64];
    uint32_t a[144], r[32];
    Dq q;
    dq_setup<kWPitch>(q, sb + kOffW + (warp_id * 16 + (lane >> 2)) * 4, phase);
    q.c[0] = neg_zero(z0);
    q.c[1] = neg_zero(z1);
    cx.sc[0] = out_scale(s0);
    cx.sc[1] = out_scale(s1);
    if (PIN) {
      const uint32_t x = (q.addr[0] ^ q.addr[1] ^ q.addr[2]) + (q.addr[3] ^ q.addr[4] ^ q.sh[0]) +
                         (q.sh[1] ^ q.sh[2] ^ q.sh[3]) + (q.sh[4] ^ cx.empty_dst);
      asm volatile("{\n.reg .pred p;\n.reg .u32 t;\nand.b32 t, %0, %1;\nsetp.eq.u32 p, t, 0;\n@p bra OK;\ntrap;\nOK:\n}" ::"r"(x), "r"(zero) : "memory");
    }
    if (EARLYB) asm volatile("bar.sync 2, 320;" ::: "memory");
    asm volatile("cp.async.wait_group 1;" ::: "memory");
    wg_sync(wg);
    dq_load<0, kPre>(a, q);
    dq_math<0, kPre>(a, q);
    if (!LATE2) {
      asm volatile("cp.async.wait_group 0;" ::: "memory");
      wg_sync(wg);
      dq_load<kPre, head_end(1) - kPre>(a, q);
    }
    if (!EARLYB) asm volatile("bar.sync 2, 320;" ::: "memory");
    tile<1, 0>(d, a, r, q, cx);
    tile<0, 1>(d, a, r, q, cx);
    tile<0, 2>(d, a, r, q, cx);
    if (wg == 0 && has_extra) {
      tile<2, 3>(d, a, r, q, cx);
      cx.out_e = reinterpret_cast<char*>(out) + ((size_t)(row_e * 4 + phase_e) * kF + n_e) * 2;
      cx.rows_e = min(kNX, kSup - row_e);
      tile<3, 4>(d, a, r, q, cx);
    } else {
      tile<0, 3>(d, a, r, q, cx);
    }
  }
}

typedef CUresult (*EncodeFn)(CUtensorMap*, CUtensorMapDataType, cuuint32_t, void*, const cuuint64_t*,
                             const cuuint64_t*, const cuuint32_t*, const cuuint32_t*, CUtensorMapInterleave,
                             CUtensorMapSwizzle, CUtensorMapL2promotion, CUtensorMapFloatOOBfill);

void make_map(EncodeFn enc, CUtensorMap* tm, CUtensorMapDataType dt, const void* base, uint64_t d0, uint64_t d1,
              uint64_t stride, uint32_t b0, uint32_t b1, CUtensorMapSwizzle sw, CUtensorMapL2promotion promo) {
  cuuint64_t dims[2] = {d0, d1};
  cuuint64_t strides[1] = {stride};
  cuuint32_t box[2] = {b0, b1};
  cuuint32_t es[2] = {1, 1};
  enc(tm, dt, 2, const_cast<void*>(base), dims, strides, box, es, CU_TENSOR_MAP_INTERLEAVE_NONE, sw, promo,
      CU_TENSOR_MAP_FLOAT_OOB_FILL_NONE);
}

}

extern "C" void kernel_launch(void* const* d_in, const int* in_sizes, int n_in, void* d_out, int out_size) {
  (void)in_sizes; (void)n_in; (void)out_size;
  static EncodeFn enc = nullptr;
  if (!enc) {
    void* fn = nullptr;
    cudaDriverEntryPointQueryResult qr;
    cudaGetDriverEntryPoint("cuTensorMapEncodeTiled", &fn, cudaEnableDefault, &qr);
    enc = (EncodeFn)fn;
    cudaFuncSetAttribute(gptq_gemm_kernel, cudaFuncAttributeMaxDynamicSharedMemorySize, kSmemBytes);
  }
  CUtensorMap x64, x52, w, we, o;
  make_map(enc, &x64, CU_TENSOR_MAP_DATA_TYPE_BFLOAT16, d_in[0], 2280, kSup, 4560, 64, 64, CU_TENSOR_MAP_SWIZZLE_128B,
           CU_TENSOR_MAP_L2_PROMOTION_L2_128B);
  make_map(enc, &x52, CU_TENSOR_MAP_DATA_TYPE_BFLOAT16, d_in[0], 2280, kSup, 4560, 64, kNX / 2,
           CU_TENSOR_MAP_SWIZZLE_128B, CU_TENSOR_MAP_L2_PROMOTION_L2_128B);
  make_map(enc, &w, CU_TENSOR_MAP_DATA_TYPE_INT32, d_in[1], kF, 57, kF * 4, 136, 8, CU_TENSOR_MAP_SWIZZLE_NONE,
           CU_TENSOR_MAP_L2_PROMOTION_L2_128B);
  make_map(enc, &we, CU_TENSOR_MAP_DATA_TYPE_INT32, d_in[1], kF, 57, kF * 4, 72, kWeRows, CU_TENSOR_MAP_SWIZZLE_NONE,
           CU_TENSOR_MAP_L2_PROMOTION_L2_128B);
  make_map(enc, &o, CU_TENSOR_MAP_DATA_TYPE_BFLOAT16, d_out, 4 * kF, kSup, 8 * kF, 64, 128, CU_TENSOR_MAP_SWIZZLE_128B,
           CU_TENSOR_MAP_L2_PROMOTION_NONE);
  gptq_gemm_kernel<<<2 * kClusters, 384, kSmemBytes>>>((const uint32_t*)d_in[1], (const __nv_bfloat16*)d_in[2],
                                                       (const __nv_bfloat16*)d_in[3], (__nv_bfloat16*)d_out, 0u, x64,
                                                       w, o, x52, we);
}
```

```cpp
#include <cuda.h>
#include <cuda_bf16.h>
#include <cuda_runtime.h>
#include <stdint.h>

namespace {

constexpr int kF = 4608;
constexpr int kSup = 512;
constexpr int kChunks = 9;
constexpr int kNX = 104;
constexpr int kClusters = 66;
constexpr int kExtraClusters = 60;

constexpr int kPre = 32;
constexpr int kLag = 4;
constexpr int kGateFirst = 6;
constexpr int kGateLast = 4;
constexpr int kDefer = 4;
constexpr int kPaceFirst = 500;
constexpr int kPace = 400;
constexpr int kSS = 2;
constexpr int kLead = 2;

constexpr int kStages = 10;
constexpr int kStageBytes = 16384;
constexpr int kWPitch = 544;
constexpr int kWePitch = 288;
constexpr int kHeadRows = (64 * kSS + 9) / 10;
constexpr int kWeRow0 = (32 * kSS - 3) / 5;
constexpr int kWeRows = 57 - kWeRow0;
constexpr int kOffOut = kStages * kStageBytes;
constexpr int kOffW = kOffOut + 2 * 16384;
constexpr int kOffAx = kOffW;
constexpr int kOffWe = kOffAx + (10 * kHeadRows + 6) * 128;
constexpr int kOffHead = kOffWe + (kWeRows + 1) * kWePitch;
constexpr int kOffZS = kOffHead + kHeadRows * 256;
constexpr int kOffZ0 = kOffZS - 512;
constexpr int kBarFull = kOffZS + 256;
constexpr int kBarEmpty = kBarFull + 8 * kStages;
constexpr int kBarWe = kBarEmpty + 8 * kStages;
constexpr int kBarDq = kBarWe + 8;
constexpr int kBarAx = kBarDq + 8;
constexpr int kBarLd = kBarAx + 8;
constexpr int kBarOutFull = kBarLd + 8;
constexpr int kBarOutFree = kBarOutFull + 16;
constexpr int kOffEnd = kBarOutFree + 16;
static_assert(kOffZ0 >= kOffW + 58 * kWPitch, "must stay clear of the packed slab");

__host__ __device__ constexpr int head_end(int c) {
  constexpr int tab[9] = {kPre, 46, 60, 74, 90, 106, 122, 132, 144};
  return tab[c > 8 ? 8 : c];
}
__host__ __device__ constexpr int last_word(int regs) { return (2 * regs - 1) / 5 > 56 ? 56 : (2 * regs - 1) / 5; }
constexpr int kFirst = last_word(head_end(2)) / 8 + 1;
__host__ __device__ constexpr int ride_step(int p) {
  int c = 0;
  while (c < 8 && last_word(head_end(c + 2)) < 8 * p) ++c;
  return c;
}
__host__ __device__ constexpr int refill_end(int c) {
  constexpr int tab[9] = {0, 0, 16, 16, 36, 56, 76, 94, 16 * (kChunks - kSS)};
  return tab[c < 0 ? 0 : c];
}
static_assert(kFirst == 3 && last_word(kPre) < 16, "front groups");

constexpr int kSmemBytes = kOffEnd;
static_assert(kSmemBytes <= 232448, "smem");

__device__ __forceinline__ void mbar_init(uint32_t bar, uint32_t cnt) {
  asm volatile("mbarrier.init.shared::cta.b64 [%0], %1;" ::"r"(bar), "r"(cnt) : "memory");
}
__device__ __forceinline__ void mbar_expect_tx(uint32_t bar, uint32_t bytes) {
  asm volatile("mbarrier.arrive.expect_tx.shared::cta.b64 _, [%0], %1;" ::"r"(bar), "r"(bytes) : "memory");
}
__device__ __forceinline__ void mbar_arrive(uint32_t bar) {
  asm volatile("mbarrier.arrive.shared::cta.b64 _, [%0];" ::"r"(bar) : "memory");
}
__device__ __forceinline__ void mbar_wait(uint32_t bar, uint32_t parity) {
  asm volatile(
      "{\n.reg .pred p;\n.reg .u32 it;\n"
      "mbarrier.try_wait.parity.shared::cta.b64 p, [%0], %1;\n"
      "@p bra DONE;\n"
      "mov.u32 it, 0;\n"
      "SPIN:\n"
      "mbarrier.try_wait.parity.shared::cta.b64 p, [%0], %1;\n"
      "@p bra DONE;\n"
      "add.u32 it, it, 1;\n"
      "setp.lt.u32 p, it, 0x100000;\n"
      "@p bra SPIN;\n"
      "trap;\n"
      "DONE:\n}" ::"r"(bar),
      "r"(parity)
      : "memory");
}
__device__ __forceinline__ void mbar_wait_lazy(uint32_t bar, uint32_t parity) {
  asm volatile(
      "{\n.reg .pred p;\n.reg .u32 it;\n"
      "mov.u32 it, 0;\n"
      "SPIN:\n"
      "mbarrier.try_wait.parity.shared::cta.b64 p, [%0], %1, 4000;\n"
      "@p bra DONE;\n"
      "add.u32 it, it, 1;\n"
      "setp.lt.u32 p, it, 0x40000;\n"
      "@p bra SPIN;\n"
      "trap;\n"
      "DONE:\n}" ::"r"(bar),
      "r"(parity)
      : "memory");
}
__device__ __forceinline__ bool elect_one() {
  uint32_t p;
  asm volatile("{\n.reg .pred q;\nelect.sync _|q, 0xffffffff;\nselp.u32 %0, 1, 0, q;\n}" : "=r"(p));
  return p;
}
__device__ __forceinline__ void tma_load_2d(uint32_t dst, const CUtensorMap* tm, uint32_t bar, int c0, int c1) {
  asm volatile(
      "cp.async.bulk.tensor.2d.shared::cluster.global.mbarrier::complete_tx::bytes [%0], [%1, {%3, %4}], [%2];" ::"r"(dst),
      "l"(tm), "r"(bar), "r"(c0), "r"(c1)
      : "memory");
}
__device__ __forceinline__ void tma_load_2d_mc(uint32_t dst, const CUtensorMap* tm, uint32_t bar, int c0, int c1) {
  asm volatile(
      "cp.async.bulk.tensor.2d.shared::cluster.global.mbarrier::complete_tx::bytes.multicast::cluster [%0], [%1, {%3, "
      "%4}], [%2], %5;" ::"r"(dst),
      "l"(tm), "r"(bar), "r"(c0), "r"(c1), "h"((uint16_t)3)
      : "memory");
}
__device__ __forceinline__ void bulk_load(uint32_t dst, const void* src, uint32_t bytes, uint32_t bar) {
  asm volatile("cp.async.bulk.shared::cluster.global.mbarrier::complete_tx::bytes [%0], [%1], %2, [%3];" ::"r"(dst),
               "l"(src), "r"(bytes), "r"(bar)
               : "memory");
}
__device__ __forceinline__ void tma_store_2d(const CUtensorMap* tm, uint32_t src, int c0, int c1) {
  asm volatile("cp.async.bulk.tensor.2d.global.shared::cta.bulk_group [%0, {%2, %3}], [%1];" ::"l"(tm), "r"(src),
               "r"(c0), "r"(c1)
               : "memory");
}
__device__ __forceinline__ void cp_async16(uint32_t dst, const void* src) {
  asm volatile("cp.async.cg.shared.global [%0], [%1], 16;" ::"r"(dst), "l"(src) : "memory");
}
__device__ __forceinline__ uint16_t lds_u16(uint32_t addr) {
  uint16_t v;
  asm volatile("ld.shared.u16 %0, [%1];" : "=h"(v) : "r"(addr));
  return v;
}
__device__ __forceinline__ void wgmma_fence() { asm volatile("wgmma.fence.sync.aligned;" ::: "memory"); }
__device__ __forceinline__ void wgmma_commit() { asm volatile("wgmma.commit_group.sync.aligned;" ::: "memory"); }
template <int N>
__device__ __forceinline__ void wgmma_wait() {
  asm volatile("wgmma.wait_group.sync.aligned %0;" ::"n"(N) : "memory");
}
__device__ __forceinline__ uint64_t smem_desc(uint32_t addr) {
  return (uint64_t)((addr & 0x3FFFF) >> 4) | (1ull << 16) | (64ull << 32) | (1ull << 62);
}
__device__ __forceinline__ uint32_t bf16x2_fma(uint32_t a, uint32_t b, uint32_t c) {
  uint32_t d;
  asm("fma.rn.bf16x2 %0, %1, %2, %3;" : "=r"(d) : "r"(a), "r"(b), "r"(c));
  return d;
}
__device__ __forceinline__ uint32_t bf16x2_mul(uint32_t a, uint32_t b) {
  uint32_t d;
  asm("mul.rn.bf16x2 %0, %1, %2;" : "=r"(d) : "r"(a), "r"(b));
  return d;
}

template <int ACC>
__device__ __forceinline__ void wgmma_rs_n128(float (&d)[64], uint32_t a0, uint32_t a1, uint32_t a2, uint32_t a3,
                                              uint64_t desc_b) {
  asm volatile(
      "{\n.reg .pred p;\nsetp.ne.b32 p, %69, 0;\n"
      "wgmma.mma_async.sync.aligned.m64n128k16.f32.bf16.bf16 {"
      "%0, %1, %2, %3, %4, %5, %6, %7, %8, %9, %10, %11, %12, %13, %14, %15, "
      "%16, %17, %18, %19, %20, %21, %22, %23, %24, %25, %26, %27, %28, %29, %30, %31, "
      "%32, %33, %34, %35, %36, %37, %38, %39, %40, %41, %42, %43, %44, %45, %46, %47, "
      "%48, %49, %50, %51, %52, %53, %54, %55, %56, %57, %58, %59, %60, %61, %62, %63"
      "}, {%64, %65, %66, %67}, %68, p, 1, 1, 0;\n}\n"
      : "+f"(d[0]), "+f"(d[1]), "+f"(d[2]), "+f"(d[3]), "+f"(d[4]), "+f"(d[5]), "+f"(d[6]), "+f"(d[7]),
        "+f"(d[8]), "+f"(d[9]), "+f"(d[10]), "+f"(d[11]), "+f"(d[12]), "+f"(d[13]), "+f"(d[14]), "+f"(d[15]),
        "+f"(d[16]), "+f"(d[17]), "+f"(d[18]), "+f"(d[19]), "+f"(d[20]), "+f"(d[21]), "+f"(d[22]), "+f"(d[23]),
        "+f"(d[24]), "+f"(d[25]), "+f"(d[26]), "+f"(d[27]), "+f"(d[28]), "+f"(d[29]), "+f"(d[30]), "+f"(d[31]),
        "+f"(d[32]), "+f"(d[33]), "+f"(d[34]), "+f"(d[35]), "+f"(d[36]), "+f"(d[37]), "+f"(d[38]), "+f"(d[39]),
        "+f"(d[40]), "+f"(d[41]), "+f"(d[42]), "+f"(d[43]), "+f"(d[44]), "+f"(d[45]), "+f"(d[46]), "+f"(d[47]),
        "+f"(d[48]), "+f"(d[49]), "+f"(d[50]), "+f"(d[51]), "+f"(d[52]), "+f"(d[53]), "+f"(d[54]), "+f"(d[55]),
        "+f"(d[56]), "+f"(d[57]), "+f"(d[58]), "+f"(d[59]), "+f"(d[60]), "+f"(d[61]), "+f"(d[62]), "+f"(d[63])
      : "r"(a0), "r"(a1), "r"(a2), "r"(a3), "l"(desc_b), "n"(ACC));
}

template <int ACC>
__device__ __forceinline__ void wgmma_rs_n48(float (&d)[64], uint32_t a0, uint32_t a1, uint32_t a2, uint32_t a3,
                                              uint64_t desc_b) {
  if (ACC) {
    asm volatile(
        "wgmma.mma_async.sync.aligned.m64n48k16.f32.bf16.bf16 {"
        "%0, %1, %2, %3, %4, %5, %6, %7, %8, %9, %10, %11, %12, %13, %14, %15, "
        "%16, %17, %18, %19, %20, %21, %22, %23"
        "}, {%24, %25, %26, %27}, %28, 1, 1, 1, 0;"
        : "+f"(d[0]), "+f"(d[1]), "+f"(d[2]), "+f"(d[3]), "+f"(d[4]), "+f"(d[5]), "+f"(d[6]), "+f"(d[7]),
          "+f"(d[8]), "+f"(d[9]), "+f"(d[10]), "+f"(d[11]), "+f"(d[12]), "+f"(d[13]), "+f"(d[14]), "+f"(d[15]),
          "+f"(d[16]), "+f"(d[17]), "+f"(d[18]), "+f"(d[19]), "+f"(d[20]), "+f"(d[21]), "+f"(d[22]), "+f"(d[23])
        : "r"(a0), "r"(a1), "r"(a2), "r"(a3), "l"(desc_b));
  } else {
    asm volatile(
        "wgmma.mma_async.sync.aligned.m64n48k16.f32.bf16.bf16 {"
        "%0, %1, %2, %3, %4, %5, %6, %7, %8, %9, %10, %11, %12, %13, %14, %15, "
        "%16, %17, %18, %19, %20, %21, %22, %23"
        "}, {%24, %25, %26, %27}, %28, 0, 1, 1, 0;"
        : "=f"(d[0]), "=f"(d[1]), "=f"(d[2]), "=f"(d[3]), "=f"(d[4]), "=f"(d[5]), "=f"(d[6]), "=f"(d[7]),
          "=f"(d[8]), "=f"(d[9]), "=f"(d[10]), "=f"(d[11]), "=f"(d[12]), "=f"(d[13]), "=f"(d[14]), "=f"(d[15]),
          "=f"(d[16]), "=f"(d[17]), "=f"(d[18]), "=f"(d[19]), "=f"(d[20]), "=f"(d[21]), "=f"(d[22]), "=f"(d[23])
        : "r"(a0), "r"(a1), "r"(a2), "r"(a3), "l"(desc_b));
  }
}

template <int ACC>
__device__ __forceinline__ void wgmma_rs_n56(float (&d)[64], uint32_t a0, uint32_t a1, uint32_t a2, uint32_t a3,
                                              uint64_t desc_b) {
  if (ACC) {
    asm volatile(
        "wgmma.mma_async.sync.aligned.m64n56k16.f32.bf16.bf16 {"
        "%0, %1, %2, %3, %4, %5, %6, %7, %8, %9, %10, %11, %12, %13, %14, %15, "
        "%16, %17, %18, %19, %20, %21, %22, %23, %24, %25, %26, %27"
        "}, {%28, %29, %30, %31}, %32, 1, 1, 1, 0;"
        : "+f"(d[24]), "+f"(d[25]), "+f"(d[26]), "+f"(d[27]), "+f"(d[28]), "+f"(d[29]), "+f"(d[30]), "+f"(d[31]),
          "+f"(d[32]), "+f"(d[33]), "+f"(d[34]), "+f"(d[35]), "+f"(d[36]), "+f"(d[37]), "+f"(d[38]), "+f"(d[39]),
          "+f"(d[40]), "+f"(d[41]), "+f"(d[42]), "+f"(d[43]), "+f"(d[44]), "+f"(d[45]), "+f"(d[46]), "+f"(d[47]),
          "+f"(d[48]), "+f"(d[49]), "+f"(d[50]), "+f"(d[51])
        : "r"(a0), "r"(a1), "r"(a2), "r"(a3), "l"(desc_b));
  } else {
    asm volatile(
        "wgmma.mma_async.sync.aligned.m64n56k16.f32.bf16.bf16 {"
        "%0, %1, %2, %3, %4, %5, %6, %7, %8, %9, %10, %11, %12, %13, %14, %15, "
        "%16, %17, %18, %19, %20, %21, %22, %23, %24, %25, %26, %27"
        "}, {%28, %29, %30, %31}, %32, 0, 1, 1, 0;"
        : "=f"(d[24]), "=f"(d[25]), "=f"(d[26]), "=f"(d[27]), "=f"(d[28]), "=f"(d[29]), "=f"(d[30]), "=f"(d[31]),
          "=f"(d[32]), "=f"(d[33]), "=f"(d[34]), "=f"(d[35]), "=f"(d[36]), "=f"(d[37]), "=f"(d[38]), "=f"(d[39]),
          "=f"(d[40]), "=f"(d[41]), "=f"(d[42]), "=f"(d[43]), "=f"(d[44]), "=f"(d[45]), "=f"(d[46]), "=f"(d[47]),
          "=f"(d[48]), "=f"(d[49]), "=f"(d[50]), "=f"(d[51])
        : "r"(a0), "r"(a1), "r"(a2), "r"(a3), "l"(desc_b));
  }
}

template <int ACC>
__device__ __forceinline__ void wgmma_ss_n48(float (&d)[64], uint64_t desc_a, uint64_t desc_b) {
  if (ACC) {
    asm volatile(
        "wgmma.mma_async.sync.aligned.m64n48k16.f32.bf16.bf16 {"
        "%0, %1, %2, %3, %4, %5, %6, %7, %8, %9, %10, %11, %12, %13, %14, %15, "
        "%16, %17, %18, %19, %20, %21, %22, %23"
        "}, %24, %25, 1, 1, 1, 1, 0;"
        : "+f"(d[0]), "+f"(d[1]), "+f"(d[2]), "+f"(d[3]), "+f"(d[4]), "+f"(d[5]), "+f"(d[6]), "+f"(d[7]),
          "+f"(d[8]), "+f"(d[9]), "+f"(d[10]), "+f"(d[11]), "+f"(d[12]), "+f"(d[13]), "+f"(d[14]), "+f"(d[15]),
          "+f"(d[16]), "+f"(d[17]), "+f"(d[18]), "+f"(d[19]), "+f"(d[20]), "+f"(d[21]), "+f"(d[22]), "+f"(d[23])
        : "l"(desc_a), "l"(desc_b));
  } else {
    asm volatile(
        "wgmma.mma_async.sync.aligned.m64n48k16.f32.bf16.bf16 {"
        "%0, %1, %2, %3, %4, %5, %6, %7, %8, %9, %10, %11, %12, %13, %14, %15, "
        "%16, %17, %18, %19, %20, %21, %22, %23"
        "}, %24, %25, 0, 1, 1, 1, 0;"
        : "=f"(d[0]), "=f"(d[1]), "=f"(d[2]), "=f"(d[3]), "=f"(d[4]), "=f"(d[5]), "=f"(d[6]), "=f"(d[7]),
          "=f"(d[8]), "=f"(d[9]), "=f"(d[10]), "=f"(d[11]), "=f"(d[12]), "=f"(d[13]), "=f"(d[14]), "=f"(d[15]),
          "=f"(d[16]), "=f"(d[17]), "=f"(d[18]), "=f"(d[19]), "=f"(d[20]), "=f"(d[21]), "=f"(d[22]), "=f"(d[23])
        : "l"(desc_a), "l"(desc_b));
  }
}

template <int ACC>
__device__ __forceinline__ void wgmma_ss_n56(float (&d)[64], uint64_t desc_a, uint64_t desc_b) {
  if (ACC) {
    asm volatile(
        "wgmma.mma_async.sync.aligned.m64n56k16.f32.bf16.bf16 {"
        "%0, %1, %2, %3, %4, %5, %6, %7, %8, %9, %10, %11, %12, %13, %14, %15, "
        "%16, %17, %18, %19, %20, %21, %22, %23, %24, %25, %26, %27"
        "}, %28, %29, 1, 1, 1, 1, 0;"
        : "+f"(d[24]), "+f"(d[25]), "+f"(d[26]), "+f"(d[27]), "+f"(d[28]), "+f"(d[29]), "+f"(d[30]), "+f"(d[31]),
          "+f"(d[32]), "+f"(d[33]), "+f"(d[34]), "+f"(d[35]), "+f"(d[36]), "+f"(d[37]), "+f"(d[38]), "+f"(d[39]),
          "+f"(d[40]), "+f"(d[41]), "+f"(d[42]), "+f"(d[43]), "+f"(d[44]), "+f"(d[45]), "+f"(d[46]), "+f"(d[47]),
          "+f"(d[48]), "+f"(d[49]), "+f"(d[50]), "+f"(d[51])
        : "l"(desc_a), "l"(desc_b));
  } else {
    asm volatile(
        "wgmma.mma_async.sync.aligned.m64n56k16.f32.bf16.bf16 {"
        "%0, %1, %2, %3, %4, %5, %6, %7, %8, %9, %10, %11, %12, %13, %14, %15, "
        "%16, %17, %18, %19, %20, %21, %22, %23, %24, %25, %26, %27"
        "}, %28, %29, 0, 1, 1, 1, 0;"
        : "=f"(d[24]), "=f"(d[25]), "=f"(d[26]), "=f"(d[27]), "=f"(d[28]), "=f"(d[29]), "=f"(d[30]), "=f"(d[31]),
          "=f"(d[32]), "=f"(d[33]), "=f"(d[34]), "=f"(d[35]), "=f"(d[36]), "=f"(d[37]), "=f"(d[38]), "=f"(d[39]),
          "=f"(d[40]), "=f"(d[41]), "=f"(d[42]), "=f"(d[43]), "=f"(d[44]), "=f"(d[45]), "=f"(d[46]), "=f"(d[47]),
          "=f"(d[48]), "=f"(d[49]), "=f"(d[50]), "=f"(d[51])
        : "l"(desc_a), "l"(desc_b));
  }
}


__host__ __device__ constexpr bool via_mul(int b) { return b & 1; }
struct Dq {
  uint32_t addr[5], sh[5];
  uint32_t c[2];
  int tj;
};
__device__ __forceinline__ uint32_t neg_zero(uint16_t z) { return bf16x2_mul((uint32_t)z * 0x10001u, 0xBC80BC80u); }
__device__ __forceinline__ uint32_t out_scale(uint16_t s) { return bf16x2_mul((uint32_t)s * 0x10001u, 0x42804280u); }

template <int PITCH>
__device__ __forceinline__ void dq_setup(Dq& q, uint32_t base, int phase) {
  q.tj = (threadIdx.x & 3) - phase;
#pragma unroll
  for (int b = 0; b < 5; ++b) {
    const int e = 4 * b + q.tj + 5;
    const int o = (e * 52) >> 8;
    q.addr[b] = base + (o - 1) * PITCH;
    q.sh[b] = 6 * (e - 5 * o);
    if (via_mul(b)) asm("shr.u32 %0, 0x1000000, %1;" : "=r"(q.sh[b]) : "r"(q.sh[b]));
  }
}
template <int R0, int NR, int PITCH = kWPitch, int DST = R0>
__device__ __forceinline__ void dq_load(uint32_t (&a)[144], const Dq& q) {
#pragma unroll
  for (int i = R0; i < R0 + NR; ++i)
    asm volatile("ld.shared.u32 %0, [%1];"
                 : "=r"(a[i - R0 + DST])
                 : "r"(q.addr[(i >> 1) % 5] + ((i >> 1) / 5) * 4 * PITCH + (i & 1) * 32));
}
template <int R0, int NR, int DST = R0>
__device__ __forceinline__ void dq_math(uint32_t (&a)[144], const Dq& q) {
#pragma unroll
  for (int i = R0; i < R0 + NR; ++i) {
    const int u = i >> 1;
    uint32_t w = a[i - R0 + DST];
    if (via_mul(u % 5)) w = __byte_perm(w * q.sh[u % 5], 0, 0x3333);
    else w = __byte_perm(w >> q.sh[u % 5], 0, 0x0000);
    w = bf16x2_fma(w & 0x00380007u, 0x7D807F00u, q.c[i & 1]);
    if (u == 0) w = q.tj < 0 ? 0u : w;
    if (u == 71) w = q.tj > 0 ? 0u : w;
    a[i - R0 + DST] = w;
  }
}

template <int C>
__device__ __forceinline__ void mma_chunk(float (&d)[64], const uint32_t (&a)[144], uint64_t desc) {
  wgmma_fence();
#pragma unroll
  for (int s = 4 * C; s < 4 * C + 4; ++s) {
    if (s == 0) wgmma_rs_n128<0>(d, a[0], a[1], a[2], a[3], desc);
    else wgmma_rs_n128<1>(d, a[4 * s], a[4 * s + 1], a[4 * s + 2], a[4 * s + 3], desc + 2 * (s & 3));
  }
  wgmma_commit();
}
template <int C>
__device__ __forceinline__ void mma_chunk_extra(float (&d)[64], const uint32_t (&a)[144], uint64_t desc0) {
  constexpr int CB = C - kLead, SA = (4 * kChunks + C) % kStages, SB = (4 * kChunks + CB + kStages) % kStages;
  wgmma_fence();
#pragma unroll
  for (int kk = 0; kk < 4; ++kk) {
    if (C < kChunks) {
      const uint64_t db = desc0 + SA * (kStageBytes / 16) + 2 * kk;
      if (C < kSS) {
        const uint64_t da = desc0 + (kOffAx + C * 8192) / 16 + 128 * kk;
        if (C == 0 && kk == 0) wgmma_ss_n48<0>(d, da, db);
        else wgmma_ss_n48<1>(d, da, db);
      } else {
        const int r = (16 * (C - kSS) + 4 * kk) % 144;
        wgmma_rs_n48<1>(d, a[r], a[r + 1], a[r + 2], a[r + 3], db);
      }
    }
    if (CB >= 0) {
      const uint64_t db = desc0 + SB * (kStageBytes / 16) + 48 * 8 + 2 * kk;
      if (CB < kSS) {
        const uint64_t da = desc0 + (kOffAx + CB * 8192) / 16 + 128 * kk;
        if (CB == 0 && kk == 0) wgmma_ss_n56<0>(d, da, db);
        else wgmma_ss_n56<1>(d, da, db);
      } else {
        const int r = (16 * (CB - kSS) + 4 * kk + 144) % 144;
        wgmma_rs_n56<1>(d, a[r], a[r + 1], a[r + 2], a[r + 3], db);
      }
    }
  }
  wgmma_commit();
}

struct Ctx {
  uint32_t sb;
  uint32_t empty_dst;
  uint64_t desc;
  int wg;
  bool extra;
  int phase_e;
  uint32_t zero;
  uint32_t sc[2];
  char* out_e;
  int rows_e;
};

template <int I>
__device__ __forceinline__ void boundary(const Ctx& cx) {
  asm volatile("{\n.reg .pred p;\nsetp.ne.s32 p, %0, %1;\n@p bra.uni OK;\ntrap;\nOK:\n}" ::"r"(cx.zero), "n"(I + 100)
               : "memory");
}

template <int G>
__device__ __forceinline__ void release(const Ctx& cx) {
  if (G + kStages >= 5 * kChunks) return;
  if ((G + kStages < 4 * kChunks || cx.extra) && (threadIdx.x & 31) < 2)
    asm volatile("mbarrier.arrive.shared::cluster.b64 _, [%0];" ::"r"(cx.empty_dst + ((G + kStages) % kStages) * 8)
                 : "memory");
}

__device__ __forceinline__ void wg_sync(int wg) {
  if (wg == 0) asm volatile("barrier.cta.sync 3, 128;" ::: "memory");
  else asm volatile("barrier.cta.sync 4, 128;" ::: "memory");
}

template <int I0, int I1, int N>
__device__ __forceinline__ void stage_rows(uint32_t (&r)[32], const Ctx& cx) {
  const int lane = threadIdx.x & 31, warp = (threadIdx.x >> 5) & 3;
  const uint32_t st = cx.sb + kOffOut + cx.wg * 16384 + ((lane & 7) + ((lane >> 4) << 3)) * 128 +
                      (((warp * 2 + ((lane >> 3) & 1)) ^ (lane & 7)) << 4);
#pragma unroll
  for (int i = I0; i < I1; ++i) {
#pragma unroll
    for (int j = 0; j < 4; ++j)
      if (4 * i + j < N / 4) r[4 * i + j] = bf16x2_mul(r[4 * i + j], cx.sc[j & 1]);
    if (4 * i + 2 < N / 4) {
      asm volatile("stmatrix.sync.aligned.m8n8.x4.trans.shared.b16 [%0], {%1, %2, %3, %4};" ::"r"(st + i * 2048),
                   "r"(r[4 * i]), "r"(r[4 * i + 1]), "r"(r[4 * i + 2]), "r"(r[4 * i + 3])
                   : "memory");
    } else {
      asm volatile("stmatrix.sync.aligned.m8n8.x2.trans.shared.b16 [%0], {%1, %2};" ::"r"(st + i * 2048), "r"(r[4 * i]),
                   "r"(r[4 * i + 1])
                   : "memory");
    }
  }
}
__device__ __forceinline__ void hand_over(const Ctx& cx) {
  asm volatile("fence.proxy.async.shared::cta;" ::: "memory");
  __syncwarp();
  if ((threadIdx.x & 31) == 0) mbar_arrive(cx.sb + kBarOutFull + cx.wg * 8);
}

template <int MODE, int T, int C>
__device__ __forceinline__ void tile_step(float (&d)[64], uint32_t (&a)[144], uint32_t (&r)[32], Dq& q, Ctx& cx) {
  constexpr int G = T * kChunks + C, S = G % kStages;
  const uint32_t sb = cx.sb;
  mbar_wait(sb + kBarFull + S * 8, (G / kStages) & 1);
  if (T > 0 && MODE != 3 && C == 0 && cx.wg == 1) asm volatile("barrier.cta.sync 1, 256;" ::: "memory");
  if (T == 3 && MODE == 0 && C == kGateLast && cx.wg == 1 && cx.extra)
    asm volatile("barrier.cta.sync 7, 256;" ::: "memory");
  if (T == 0 && C == kGateFirst && cx.wg == 1) asm volatile("barrier.cta.sync 6, 256;" ::: "memory");
  if (MODE == 3) mma_chunk_extra<C>(d, a, cx.desc);
  else mma_chunk<C>(d, a, cx.desc + S * (kStageBytes / 16));
  if (T > 0 && MODE != 3 && C == kLag && cx.wg == 0) asm volatile("barrier.cta.arrive 1, 256;" ::: "memory");
  if (MODE == 2 && C == 8) asm volatile("barrier.cta.arrive 7, 256;" ::: "memory");
  if (T == 0 && C == 8 && cx.wg == 0) asm volatile("barrier.cta.arrive 6, 256;" ::: "memory");
  if (T > 0 && C == 0) {
    boundary<300 + T + 10 * MODE>(cx);
    stage_rows<8 - kDefer, 8, 128>(r, cx);
    hand_over(cx);
  }
  if (MODE == 1 && C < 8) {
    boundary<C>(cx);
    dq_math<head_end(C) % 144, head_end(C + 1) - head_end(C)>(a, q);
  }
  if (MODE == 2 && C == 0) {
    const int col = ((threadIdx.x >> 5) & 3) * 16 + ((threadIdx.x & 31) >> 2);
    dq_setup<kWePitch>(q, sb + kOffWe - kWeRow0 * kWePitch + col * 4, cx.phase_e);
    mbar_wait(sb + kBarWe, 0);
    q.c[0] = neg_zero(lds_u16(sb + kOffZS + col * 2));
    q.c[1] = neg_zero(lds_u16(sb + kOffZS + col * 2 + 16));
  }
  if (MODE == 3 && C == 2) {
    boundary<90>(cx);
    const int col = (threadIdx.x >> 5) * 16 + ((threadIdx.x & 31) >> 2);
    cx.sc[0] = out_scale(lds_u16(sb + kOffZS + 128 + col * 2));
    cx.sc[1] = out_scale(lds_u16(sb + kOffZS + 128 + col * 2 + 16));
  }
  if (MODE == 2 && C == 8) mbar_wait(sb + kBarAx, 0);
  if (MODE == 2 && C >= 2) {
    dq_load<16 * kSS + refill_end(C - 1), refill_end(C) - refill_end(C - 1), kWePitch, refill_end(C - 1)>(a, q);
    dq_math<16 * kSS + refill_end(C - 1), refill_end(C) - refill_end(C - 1), refill_end(C - 1)>(a, q);
  }
  if (C > 0 && MODE != 3) wgmma_wait<1>();
  if (MODE == 1 && C < 7) dq_load<head_end(C + 1) % 144, head_end(C + 2) - head_end(C + 1)>(a, q);
  if (C > 0 && MODE != 3) release<G - 1>(cx);
}

template <int I0, int I1>
__device__ __forceinline__ void final_rows(const Ctx& cx) {
  asm volatile("barrier.cta.sync 3, 128;" ::: "memory");
  const int row = threadIdx.x >> 3, c = threadIdx.x & 7;
  const uint32_t src = cx.sb + kOffOut + row * 128 + ((c ^ (row & 7)) << 4);
  char* dst = cx.out_e + (size_t)row * (8 * kF) + c * 16;
  uint4 v[I1 - I0];
#pragma unroll
  for (int i = I0; i < I1; ++i)
    asm volatile("ld.shared.v4.u32 {%0, %1, %2, %3}, [%4];"
                 : "=r"(v[i - I0].x), "=r"(v[i - I0].y), "=r"(v[i - I0].z), "=r"(v[i - I0].w)
                 : "r"(src + i * 2048));
#pragma unroll
  for (int i = I0; i < I1; ++i)
    if (i < 6 || row < cx.rows_e - 96)
      asm volatile("st.global.v4.u32 [%0], {%1, %2, %3, %4};" ::"l"(dst + (size_t)i * 16 * 8 * kF), "r"(v[i - I0].x),
                   "r"(v[i - I0].y), "r"(v[i - I0].z), "r"(v[i - I0].w)
                   : "memory");
}

template <int MODE, int T>
__device__ __forceinline__ void tile(float (&d)[64], uint32_t (&a)[144], uint32_t (&r)[32], Dq& q, Ctx& cx) {
  cx.sb += cx.zero;
  cx.desc += cx.zero;
  const uint32_t sb = cx.sb;
  tile_step<MODE, T, 0>(d, a, r, q, cx);
  tile_step<MODE, T, 1>(d, a, r, q, cx);
  tile_step<MODE, T, 2>(d, a, r, q, cx);
  tile_step<MODE, T, 3>(d, a, r, q, cx);
  tile_step<MODE, T, 4>(d, a, r, q, cx);
  tile_step<MODE, T, 5>(d, a, r, q, cx);
  tile_step<MODE, T, 6>(d, a, r, q, cx);
  tile_step<MODE, T, 7>(d, a, r, q, cx);
  tile_step<MODE, T, 8>(d, a, r, q, cx);
  if (MODE == 1 && (threadIdx.x & 31) == 0) mbar_arrive(sb + kBarDq);
  if (MODE == 3) {
    static_assert(kLead == 2, "trailing groups");
    mma_chunk_extra<9>(d, a, cx.desc);
    mma_chunk_extra<10>(d, a, cx.desc);
    mbar_wait(sb + kBarOutFree, 1);
    wgmma_wait<kLead>();
#pragma unroll
    for (int i = 0; i < 24; ++i) asm volatile("" : "+f"(d[i])::"memory");
#pragma unroll
    for (int i = 0; i < 12; ++i)
      asm("cvt.rn.bf16x2.f32 %0, %1, %2;" : "=r"(r[i]) : "f"(d[2 * i + 1]), "f"(d[2 * i]));
    stage_rows<0, 3, kNX>(r, cx);
    final_rows<0, 3>(cx);
    boundary<401>(cx);
    wgmma_wait<0>();
#pragma unroll
    for (int i = 24; i < 52; ++i) asm volatile("" : "+f"(d[i])::"memory");
#pragma unroll
    for (int i = 12; i < 26; ++i)
      asm("cvt.rn.bf16x2.f32 %0, %1, %2;" : "=r"(r[i]) : "f"(d[2 * i + 1]), "f"(d[2 * i]));
    stage_rows<3, 7, kNX>(r, cx);
    final_rows<3, 7>(cx);
    return;
  }
  if (T > 0) mbar_wait(sb + kBarOutFree + cx.wg * 8, (T - 1) & 1);
  wgmma_wait<0>();
#pragma unroll
  for (int i = 0; i < 64; ++i) asm volatile("" : "+f"(d[i])::"memory");
  release<T * kChunks + 8>(cx);
#pragma unroll
  for (int i = 0; i < 32; ++i)
    asm("cvt.rn.bf16x2.f32 %0, %1, %2;" : "=r"(r[i]) : "f"(d[2 * i + 1]), "f"(d[2 * i]));
  boundary<200 + T + 10 * MODE>(cx);
  constexpr bool last = MODE == 0 && T == 3;
  stage_rows<0, last ? 8 : 8 - kDefer, 128>(r, cx);
  if (last) hand_over(cx);
}

__global__ void __cluster_dims__(2, 1, 1) __launch_bounds__(384, 1)
    gptq_gemm_kernel(const uint32_t* __restrict__ qw, const __nv_bfloat16* __restrict__ scales,
                     const __nv_bfloat16* __restrict__ zeros, __nv_bfloat16* __restrict__ out, const uint32_t zero,
                     const __grid_constant__ CUtensorMap tm_x64, const __grid_constant__ CUtensorMap tm_w,
                     const __grid_constant__ CUtensorMap tm_out, const __grid_constant__ CUtensorMap tm_x52,
                     const __grid_constant__ CUtensorMap tm_we) {
  extern __shared__ __align__(1024) uint8_t smem[];
  const uint32_t sb = (uint32_t)__cvta_generic_to_shared(smem);
  const int cid = blockIdx.x >> 1, rank = blockIdx.x & 1;
  const int phase = cid & 3, n_own = (cid >> 2) * 256 + rank * 128;
  const int warp_id = __shfl_sync(0xffffffffu, (int)(threadIdx.x >> 5), 0);

  if (warp_id < 8) {
    asm volatile("barrier.cluster.arrive.relaxed.aligned;" ::: "memory");
    const uint32_t tid = threadIdx.x, r = (tid >> 4) & 7, c4 = (tid & 15) + ((tid >> 3) & 16);
    const uint32_t* src = qw + (r * kF + n_own + c4 * 4);
    const uint32_t dst = sb + kOffW + r * kWPitch + c4 * 16;
    cp_async16(dst, src);
    cp_async16(dst + 8 * kWPitch, src + 8 * kF);
    if ((tid & 127) < 16)
      cp_async16(sb + kOffZ0 + (tid >> 7) * 256 + (tid & 15) * 16,
                 ((tid & 8) ? scales : zeros) + (n_own + (tid >> 7) * 64 + (tid & 7) * 8));
    asm volatile("cp.async.commit_group;" ::: "memory");
    cp_async16(dst + 16 * kWPitch, src + 16 * kF);
    asm volatile("cp.async.commit_group;" ::: "memory");
  } else if (warp_id != 8) {
    asm volatile("barrier.cluster.arrive.relaxed.aligned;" ::: "memory");
    asm volatile("prefetch.tensormap [%0];" ::"l"(&tm_x64) : "memory");
  }
  const int wg = warp_id >> 2;
  const int lane = threadIdx.x & 31;

  const bool has_extra = cid < kExtraClusters;
  const int ue = kClusters + cid / 10;
  const int phase_e = ue & 3, n_e = (ue >> 2) * 256 + ((cid / 5) & 1) * 128 + rank * 64, row_e = (cid % 5) * kNX;

  if (wg == 2) {
    asm volatile("setmaxnreg.dec.sync.aligned.u32 24;");
    if (warp_id >= 10) {
      asm volatile("barrier.cta.sync 5, 128;" ::: "memory");
      if (has_extra) {
        const int h = threadIdx.x - 320, c4 = h & 15;
        const int colx = n_e + c4 * 4;
        mbar_wait_lazy(sb + kBarDq, 0);
        if (warp_id == 11 && elect_one()) {
          mbar_expect_tx(sb + kBarWe, kWeRows * kWePitch + 256);
          tma_load_2d(sb + kOffWe, &tm_we, sb + kBarWe, n_e, kWeRow0);
          bulk_load(sb + kOffZS, zeros + n_e, 128, sb + kBarWe);
          bulk_load(sb + kOffZS + 128, scales + n_e, 128, sb + kBarWe);
        }
        __syncwarp();
        uint32_t src = sb + kOffHead + (h >> 4) * 256 + c4 * 16;
#pragma unroll
        for (int i = 0; i < (kHeadRows + 3) / 4; ++i)
          if (4 * i + 3 < kHeadRows || 4 * i + (h >> 4) < kHeadRows)
            cp_async16(src + i * 1024, qw + ((h >> 4) + 4 * i) * kF + colx);
        const uint2 z2 = __ldg(reinterpret_cast<const uint2*>(zeros + colx));
        const uint32_t c[2] = {bf16x2_mul(z2.x, 0xBC80BC80u), bf16x2_mul(z2.y, 0xBC80BC80u)};
        if (h < 16 * phase_e)
          asm volatile("st.shared.v4.u32 [%0], {%1, %1, %1, %1};" ::"r"(sb + kOffAx + h * 16), "r"(0u) : "memory");
        uint32_t row = sb + kOffAx + (10 * (h >> 4) + 2 * phase_e) * 128 + c4 * 8;
        const uint32_t src_end = sb + kOffHead + kHeadRows * 256;
        asm volatile("cp.async.wait_all;" ::: "memory");
#pragma unroll 1
        for (; src < src_end; src += 1024, row += 40 * 128) {
          uint4 w;
          asm volatile("ld.shared.v4.u32 {%0, %1, %2, %3}, [%4];"
                       : "=r"(w.x), "=r"(w.y), "=r"(w.z), "=r"(w.w)
                       : "r"(src)
                       : "memory");
          uint32_t win[2], ad;
#pragma unroll
          for (int i = 0; i < 10; ++i) {
            constexpr uint32_t sel[4] = {0x5410, 0x6521, 0x7632, 0x7733};
            constexpr int pos[10] = {0, 3, 2, 1, 4, 3, 2, 5, 0, 3};
            if (i == 0 || i == 3 || i == 6 || i == 8) {
              const uint32_t se = sel[i == 0 ? 0 : i == 3 ? 1 : i == 6 ? 2 : 3];
              win[0] = __byte_perm(w.x, w.y, se);
              win[1] = __byte_perm(w.z, w.w, se);
            }
            uint32_t v[2];
#pragma unroll
            for (int j = 0; j < 2; ++j) {
              const uint32_t f = ((i == 2 || i == 5) ? win[j] >> 4 : win[j]) & (0x00070007u << pos[i]);
              v[j] = bf16x2_fma(f, 0x7F007F00u - pos[i] * 0x00800080u, c[j]);
            }
            if ((i & 1) == 0) {
              asm volatile("{\n.reg .u32 t;\nadd.u32 %0, %1, %2;\nshr.u32 t, %0, 3;\nlop3.b32 %0, %0, t, 0x70, 0x78;\n}"
                           : "=r"(ad)
                           : "r"(row), "r"(i * 128));
              asm volatile("st.shared.v2.u32 [%0], {%1, %2};" ::"r"(ad), "r"(v[0]), "r"(v[1]) : "memory");
            } else {
              asm volatile("st.shared.v2.u32 [%0+128], {%1, %2};" ::"r"(ad ^ 16), "r"(v[0]), "r"(v[1]) : "memory");
            }
          }
        }
        asm volatile("fence.proxy.async.shared::cta;" ::: "memory");
        __syncwarp();
        if (lane == 0) mbar_arrive(sb + kBarAx);
      }
    } else if (warp_id == 9) {
      if (elect_one()) {
#pragma unroll
        for (int i = 0; i < kStages; ++i) mbar_init(sb + kBarEmpty + 8 * i, 16);
        mbar_init(sb + kBarWe, 1);
        mbar_init(sb + kBarDq, 8);
        mbar_init(sb + kBarAx, 2);
        mbar_init(sb + kBarLd, 1);
        mbar_init(sb + kBarOutFull, 4);
        mbar_init(sb + kBarOutFull + 8, 4);
        mbar_init(sb + kBarOutFree, 1);
        mbar_init(sb + kBarOutFree + 8, 1);
        asm volatile("fence.mbarrier_init.release.cluster;" ::: "memory");
        asm volatile("prefetch.tensormap [%0];" ::"l"(&tm_w) : "memory");
      }
      __syncwarp();
      asm volatile("barrier.cta.arrive 2, 320;" ::: "memory");
      asm volatile("barrier.cta.sync 5, 128;" ::: "memory");
      if (elect_one()) {
#pragma unroll 1
        for (int i = 0; i < 8; ++i) {
          const int w = i & 1, t = i >> 1;
          if (i == 7) mbar_wait(sb + kBarOutFull + w * 8, t & 1);
          else mbar_wait_lazy(sb + kBarOutFull + w * 8, t & 1);
          if (i == 6) mbar_wait_lazy(sb + kBarLd, 0);
          tma_store_2d(&tm_out, sb + kOffOut + w * 16384, phase * kF + n_own + w * 64, t * 128);
          asm volatile("cp.async.bulk.commit_group;" ::: "memory");
          if (i < 7) {
            asm volatile("cp.async.bulk.wait_group.read 0;" ::: "memory");
            mbar_arrive(sb + kBarOutFree + w * 8);
          }
        }
        asm volatile("cp.async.bulk.wait_group.read 0;" ::: "memory");
      }
    } else {
      uint32_t t0;
      {
        const bool leader = elect_one();
        if (leader) {
#pragma unroll
          for (int i = 0; i < kStages; ++i) mbar_init(sb + kBarFull + 8 * i, 1);
          asm volatile("fence.mbarrier_init.release.cluster;" ::: "memory");
        }
        __syncwarp();
        asm volatile("barrier.cluster.arrive.relaxed.aligned;" ::: "memory");
        asm volatile("barrier.cluster.wait.aligned;" ::: "memory");
        if (leader) {
          mbar_expect_tx(sb + kBarFull, kStageBytes);
          tma_load_2d_mc(sb + rank * 8192, &tm_x64, sb + kBarFull, phase * 568, rank * 64);
        }
        asm volatile("mov.u32 %0, %clock;" : "=r"(t0));
        __syncwarp();
        asm volatile("barrier.cta.arrive 2, 320;" ::: "memory");
        asm volatile("barrier.cta.sync 5, 128;" ::: "memory");
      }
      if (elect_one()) {
#pragma unroll
        for (int g = 1; g < kStages; ++g) {
          const uint32_t full = sb + kBarFull + g * 8;
          uint32_t t;
          for (;;) {
            asm volatile("mov.u32 %0, %clock;" : "=r"(t));
            if (t - t0 >= kPaceFirst + (g - 1) * kPace) break;
            __nanosleep(50);
          }
          uint32_t bytes = kStageBytes;
#pragma unroll
          for (int p = kFirst; p < 8; ++p)
            if (ride_step(p) == g) bytes += p < 7 ? 8 * kWPitch : 512;
          mbar_expect_tx(full, bytes);
          tma_load_2d_mc(sb + g * kStageBytes + rank * 8192, &tm_x64, full, phase * 568 + (g % kChunks) * 64,
                         rank * 64 + (g / kChunks) * 128);
#pragma unroll
          for (int p = kFirst; p < 8; ++p)
            if (ride_step(p) == g) {
              if (p < 7) tma_load_2d(sb + kOffW + p * 8 * kWPitch, &tm_w, full, n_own, p * 8);
              else bulk_load(sb + kOffW + 56 * kWPitch, qw + 56 * kF + n_own, 512, full);
            }
        }
        const int total = has_extra ? 5 * kChunks : 4 * kChunks;
        int c = kStages % kChunks, row = rank * 64 + (kStages / kChunks) * 128;
        uint32_t stage = 0, parity = 0;
#pragma unroll 1
        for (int g = kStages; g < total; ++g) {
          const uint32_t full = sb + kBarFull + stage * 8, dst = sb + stage * kStageBytes;
          mbar_wait_lazy(sb + kBarEmpty + stage * 8, parity);
          if (g < 4 * kChunks) {
            mbar_expect_tx(full, kStageBytes);
            tma_load_2d_mc(dst + rank * 8192, &tm_x64, full, phase * 568 + c * 64, row);
          } else {
            mbar_expect_tx(full, kNX * 128);
            tma_load_2d_mc(dst + rank * (kNX * 64), &tm_x52, full, phase_e * 568 + c * 64, row_e + rank * (kNX / 2));
          }
          if (++c == kChunks) { c = 0; row += 128; }
          if (++stage == kStages) { stage = 0; parity ^= 1; }
        }
        mbar_arrive(sb + kBarLd);
      }
    }
  } else {
    asm volatile("setmaxnreg.inc.sync.aligned.u32 240;");
    Ctx cx;
    cx.sb = sb;
    cx.wg = wg;
    cx.extra = has_extra;
    cx.phase_e = phase_e;
    cx.zero = zero;
    cx.desc = smem_desc(sb);
    asm("mapa.shared::cluster.u32 %0, %1, %2;" : "=r"(cx.empty_dst) : "r"(sb + kBarEmpty), "r"(lane & 1));
    float d[64];
    uint32_t a[144], r[32];
    Dq q;
    dq_setup<kWPitch>(q, sb + kOffW + (warp_id * 16 + (lane >> 2)) * 4, phase);
    asm volatile("barrier.cta.sync 2, 320;" ::: "memory");
    asm volatile("cp.async.wait_group 1;" ::: "memory");
    wg_sync(wg);
    {
      const uint32_t zs = sb + kOffZ0 + wg * 256 + ((warp_id & 3) * 16 + (lane >> 2)) * 2;
      q.c[0] = neg_zero(lds_u16(zs));
      q.c[1] = neg_zero(lds_u16(zs + 16));
      cx.sc[0] = out_scale(lds_u16(zs + 128));
      cx.sc[1] = out_scale(lds_u16(zs + 144));
    }
    dq_load<0, kPre>(a, q);
    dq_math<0, kPre>(a, q);
    asm volatile("cp.async.wait_group 0;" ::: "memory");
    wg_sync(wg);
    dq_load<kPre, head_end(1) - kPre>(a, q);
    tile<1, 0>(d, a, r, q, cx);
    tile<0, 1>(d, a, r, q, cx);
    tile<0, 2>(d, a, r, q, cx);
    if (wg == 0 && has_extra) {
      tile<2, 3>(d, a, r, q, cx);
      cx.out_e = reinterpret_cast<char*>(out) + ((size_t)(row_e * 4 + phase_e) * kF + n_e) * 2;
      cx.rows_e = min(kNX, kSup - row_e);
      tile<3, 4>(d, a, r, q, cx);
    } else {
      tile<0, 3>(d, a, r, q, cx);
    }
  }
}

typedef CUresult (*EncodeFn)(CUtensorMap*, CUtensorMapDataType, cuuint32_t, void*, const cuuint64_t*,
                             const cuuint64_t*, const cuuint32_t*, const cuuint32_t*, CUtensorMapInterleave,
                             CUtensorMapSwizzle, CUtensorMapL2promotion, CUtensorMapFloatOOBfill);

void make_map(EncodeFn enc, CUtensorMap* tm, CUtensorMapDataType dt, const void* base, uint64_t d0, uint64_t d1,
              uint64_t stride, uint32_t b0, uint32_t b1, CUtensorMapSwizzle sw, CUtensorMapL2promotion promo) {
  cuuint64_t dims[2] = {d0, d1};
  cuuint64_t strides[1] = {stride};
  cuuint32_t box[2] = {b0, b1};
  cuuint32_t es[2] = {1, 1};
  enc(tm, dt, 2, const_cast<void*>(base), dims, strides, box, es, CU_TENSOR_MAP_INTERLEAVE_NONE, sw, promo,
      CU_TENSOR_MAP_FLOAT_OOB_FILL_NONE);
}

}

extern "C" void kernel_launch(void* const* d_in, const int* in_sizes, int n_in, void* d_out, int out_size) {
  (void)in_sizes; (void)n_in; (void)out_size;
  static EncodeFn enc = nullptr;
  if (!enc) {
    void* fn = nullptr;
    cudaDriverEntryPointQueryResult qr;
    cudaGetDriverEntryPoint("cuTensorMapEncodeTiled", &fn, cudaEnableDefault, &qr);
    enc = (EncodeFn)fn;
    cudaFuncSetAttribute(gptq_gemm_kernel, cudaFuncAttributeMaxDynamicSharedMemorySize, kSmemBytes);
  }
  CUtensorMap x64, x52, w, we, o;
  make_map(enc, &x64, CU_TENSOR_MAP_DATA_TYPE_BFLOAT16, d_in[0], 2280, kSup, 4560, 64, 64, CU_TENSOR_MAP_SWIZZLE_128B,
           CU_TENSOR_MAP_L2_PROMOTION_L2_128B);
  make_map(enc, &x52, CU_TENSOR_MAP_DATA_TYPE_BFLOAT16, d_in[0], 2280, kSup, 4560, 64, kNX / 2,
           CU_TENSOR_MAP_SWIZZLE_128B, CU_TENSOR_MAP_L2_PROMOTION_L2_128B);
  make_map(enc, &w, CU_TENSOR_MAP_DATA_TYPE_INT32, d_in[1], kF, 57, kF * 4, 136, 8, CU_TENSOR_MAP_SWIZZLE_NONE,
           CU_TENSOR_MAP_L2_PROMOTION_L2_128B);
  make_map(enc, &we, CU_TENSOR_MAP_DATA_TYPE_INT32, d_in[1], kF, 57, kF * 4, 72, kWeRows, CU_TENSOR_MAP_SWIZZLE_NONE,
           CU_TENSOR_MAP_L2_PROMOTION_L2_128B);
  make_map(enc, &o, CU_TENSOR_MAP_DATA_TYPE_BFLOAT16, d_out, 4 * kF, kSup, 8 * kF, 64, 128, CU_TENSOR_MAP_SWIZZLE_128B,
           CU_TENSOR_MAP_L2_PROMOTION_NONE);
  gptq_gemm_kernel<<<2 * kClusters, 384, kSmemBytes>>>((const uint32_t*)d_in[1], (const __nv_bfloat16*)d_in[2],
                                                       (const __nv_bfloat16*)d_in[3], (__nv_bfloat16*)d_out, 0u, x64,
                                                       w, o, x52, we);
}
```
